```python
import torch

def _softmax(x, axis=-1):
    return torch.softmax(x, dim=axis)
def _gelu(x):
    return torch.nn.functional.gelu(x, approximate="tanh")
def _silu(x):
    return torch.nn.functional.silu(x)
def _sigmoid(x):
    return torch.sigmoid(x)
def _layernorm(x, axis=-1, eps=1e-5):
    m = x.mean(dim=axis, keepdim=True)
    v = x.var(dim=axis, keepdim=True, unbiased=False)
    return (x - m) / torch.sqrt(v + eps)
def _scatter_add(tgt, idx, src, axis=0):
    return tgt.clone().index_add_(axis, idx, src)
def _segment_sum(src, seg, n):
    out = torch.zeros((n,) + src.shape[1:], dtype=src.dtype)
    return out.index_add_(0, seg, src)
def _pad(x, pw):
    flat = tuple(v for pair in reversed(pw) for v in pair)
    return torch.nn.functional.pad(x, flat)

kernel_name = 'recurrent_scan__mha_block_cached__glu_gated_bilinear__decode'

def setup_inputs():

    _w = (lambda a: (lambda t: t.to(torch.bfloat16) if t.is_floating_point() else t)(torch.as_tensor(a)))
    def _A_setup():
        B, Sq, D = 8, 1, 512
        H, Sk, Dh = 32, 4096, 128
        return {
            "x": _w((lambda *s: torch.randn(*s, dtype=torch.bfloat16) * 0.2)(B, Sq, D)),
            "k_cache": _w((lambda *s: torch.randn(*s, dtype=torch.bfloat16) * 1.6)(B, H, Sk, Dh)),
            "v_cache": _w((lambda *s: torch.randn(*s, dtype=torch.bfloat16) * 1.6)(B, H, Sk, Dh)),
            "wq": _w((lambda *s: torch.randn(*s, dtype=torch.bfloat16) * 1.6)(D, H * Dh) * (D ** -0.5)),
            "wo": _w((lambda *s: torch.randn(*s, dtype=torch.bfloat16) * 1.6)(H * Dh, D) * ((H * Dh) ** -0.5)),
        }
    _A_in = _A_setup()

    def _B_setup():
        B, S, D, F = 8, 1, 512, 1792
        return {
            "x": _w((lambda *s: torch.randn(*s, dtype=torch.bfloat16) * 0.2)(B, S, D)),
            "w_gate": _w((lambda *s: torch.randn(*s, dtype=torch.bfloat16) * 0.8)(D, F) * (D ** -0.5)),
            "w_up": _w((lambda *s: torch.randn(*s, dtype=torch.bfloat16) * 0.8)(D, F) * (D ** -0.5)),
            "w_down": _w((lambda *s: torch.randn(*s, dtype=torch.bfloat16) * 0.8)(F, D) * (F ** -0.5)),
        }
    _B_in = _B_setup()

    return {
        "A_x": _A_in["x"],
        "A_k_cache": _A_in["k_cache"],
        "A_v_cache": _A_in["v_cache"],
        "A_wq": _A_in["wq"],
        "A_wo": _A_in["wo"],
        "B_x": _B_in["x"],
        "B_w_gate": _B_in["w_gate"],
        "B_w_up": _B_in["w_up"],
        "B_w_down": _B_in["w_down"],
    }

def reference(A_x, A_k_cache, A_v_cache, A_wq, A_wo, B_x, B_w_gate, B_w_up, B_w_down):
    def _A_ref(x, k_cache, v_cache, wq, wo):
        B, Sq, D = x.shape
        H, Dh = 32, 128
        q = (lambda x, *d: x.permute(*d))((x @ wq).reshape(B, Sq, H, Dh), 0, 2, 1, 3)
        scores = torch.einsum("bhqd,bhkd->bhqk", q, k_cache) * (Dh ** -0.5)
        p = _softmax(scores, axis=-1)
        o = torch.einsum("bhqk,bhkd->bhqd", p, v_cache)
        return (lambda x, *d: x.permute(*d))(o, 0, 2, 1, 3).reshape(B, Sq, H * Dh) @ wo

    def _B_ref(x, w_gate, w_up, w_down):
        g = torch.einsum("bsd,df->bsf", x, w_gate)
        u = torch.einsum("bsd,df->bsf", x, w_up)
        h = g * u
        return torch.einsum("bsf,fd->bsd", h, w_down)

    x = A_x
    xn = _layernorm(x, axis=-1)
    s = _A_ref(xn, A_k_cache, A_v_cache, A_wq, A_wo)
    g = _silu(_B_ref(xn, B_w_gate, B_w_up, B_w_down))
    return x + s * g
```

```cpp
#include <cuda_runtime.h>
#include <cuda_bf16.h>
#include <stdint.h>

#define DEPTH1 2
#define DEPTH_SWITCH 8
#define DEPTH2 4
#define PACE_GAIN 30
#define PACE_MAX 6000
#define NPRE 4

namespace {

typedef __nv_bfloat16 bf16;

constexpr int DM = 512, NH = 32, SK = 4096, DH = 128, FF = 1792;
constexpr int NCTA = 128, NTHREADS = 384;
constexpr int TILE_BYTES = 32768, STAGES = 6, TILES = SK * DH * 2 / TILE_BYTES;
constexpr int SPIN_LIMIT = 1 << 22;

constexpr int XN_STRIDE = DM * 2 + 64;
constexpr int SM_P = STAGES * TILE_BYTES;
constexpr int SM_XN = SM_P + SK * 2;
constexpr int SM_RED = SM_XN + 8 * XN_STRIDE;
constexpr int SM_Q = SM_RED + 8 * DH * 4;
constexpr int SM_O = SM_Q + 2 * DH * 2;
constexpr int SM_STAT = SM_O + DH * 2;
constexpr int SM_EPOCH = SM_STAT + 64;
constexpr int SM_FULL = SM_EPOCH + 16;
constexpr int SM_EMPTY = SM_FULL + STAGES * 8;
constexpr int SM_LAST = SM_EMPTY + STAGES * 8;
constexpr int SM_TOTAL = SM_LAST + 16;

struct Scratch {
    uint4 qx[NH * 4 * 4 * 64];
    uint4 hx[8 * FF / 4];
    uint4 fx[4 * 32 * 4 * 8];
    uint4 sx[8 * 32 * NH * 4];
    unsigned epoch;
    unsigned pad[63];
    unsigned progress;
};
__device__ Scratch g_scratch;

#define PROF(cond, slot)

__device__ __forceinline__ void mbar_init(uint32_t bar, uint32_t count) {
    asm volatile("mbarrier.init.shared::cta.b64 [%0], %1;" :: "r"(bar), "r"(count) : "memory");
}
__device__ __forceinline__ void mbar_expect_tx(uint32_t bar, uint32_t bytes) {
    asm volatile("mbarrier.arrive.expect_tx.shared::cta.b64 _, [%0], %1;" :: "r"(bar), "r"(bytes) : "memory");
}
__device__ __forceinline__ void mbar_arrive(uint32_t bar) {
    asm volatile("mbarrier.arrive.shared::cta.b64 _, [%0];" :: "r"(bar) : "memory");
}
__device__ __forceinline__ void mbar_wait(uint32_t bar, uint32_t parity) {
    uint32_t ok;
    int it = 0;
    do {
        asm volatile("{ .reg .pred p; mbarrier.try_wait.parity.shared::cta.b64 p, [%1], %2; selp.u32 %0, 1, 0, p; }"
                     : "=r"(ok) : "r"(bar), "r"(parity) : "memory");
    } while (!ok && ++it < SPIN_LIMIT);
}
__device__ __forceinline__ void bulk_load(uint32_t dst, const void* src, uint32_t bytes, uint32_t bar, uint64_t pol) {
    asm volatile("cp.async.bulk.shared::cluster.global.mbarrier::complete_tx::bytes.L2::cache_hint [%0], [%1], %2, [%3], %4;"
                 :: "r"(dst), "l"(src), "r"(bytes), "r"(bar), "l"(pol) : "memory");
}
__device__ __forceinline__ void cons_sync() { asm volatile("bar.sync 1, 256;" ::: "memory"); }

__device__ __forceinline__ uint4 lds128(uint32_t a) {
    uint4 v;
    asm volatile("ld.shared.v4.u32 {%0,%1,%2,%3}, [%4];" : "=r"(v.x), "=r"(v.y), "=r"(v.z), "=r"(v.w) : "r"(a) : "memory");
    return v;
}
__device__ __forceinline__ uint32_t lds32(uint32_t a) {
    uint32_t v;
    asm volatile("ld.shared.u32 %0, [%1];" : "=r"(v) : "r"(a) : "memory");
    return v;
}
__device__ __forceinline__ float2 lds64f(uint32_t a) {
    float2 v;
    asm volatile("ld.shared.v2.f32 {%0,%1}, [%2];" : "=f"(v.x), "=f"(v.y) : "r"(a) : "memory");
    return v;
}
__device__ __forceinline__ void sts128(uint32_t a, uint4 v) {
    asm volatile("st.shared.v4.u32 [%0], {%1,%2,%3,%4};" :: "r"(a), "r"(v.x), "r"(v.y), "r"(v.z), "r"(v.w) : "memory");
}
__device__ __forceinline__ void sts64f(uint32_t a, float x, float y) {
    asm volatile("st.shared.v2.f32 [%0], {%1,%2};" :: "r"(a), "f"(x), "f"(y) : "memory");
}
__device__ __forceinline__ void sts32(uint32_t a, uint32_t v) {
    asm volatile("st.shared.u32 [%0], %1;" :: "r"(a), "r"(v) : "memory");
}
__device__ __forceinline__ void sts16(uint32_t a, uint32_t v) {
    asm volatile("st.shared.u16 [%0], %1;" :: "r"(a), "h"((uint16_t)v) : "memory");
}
__device__ __forceinline__ uint4 ldsm4(uint32_t a) {
    uint4 v;
    asm volatile("ldmatrix.sync.aligned.m8n8.x4.shared.b16 {%0,%1,%2,%3}, [%4];"
                 : "=r"(v.x), "=r"(v.y), "=r"(v.z), "=r"(v.w) : "r"(a) : "memory");
    return v;
}
__device__ __forceinline__ uint4 ldsm4t(uint32_t a) {
    uint4 v;
    asm volatile("ldmatrix.sync.aligned.m8n8.x4.trans.shared.b16 {%0,%1,%2,%3}, [%4];"
                 : "=r"(v.x), "=r"(v.y), "=r"(v.z), "=r"(v.w) : "r"(a) : "memory");
    return v;
}
__device__ __forceinline__ void cp_async16(uint32_t dst, const void* src) {
    asm volatile("cp.async.cg.shared.global [%0], [%1], 16;" :: "r"(dst), "l"(src) : "memory");
}
__device__ __forceinline__ uint4 ldg128(const void* p) {
    uint4 v;
    asm volatile("ld.global.nc.L1::no_allocate.v4.u32 {%0,%1,%2,%3}, [%4];" : "=r"(v.x), "=r"(v.y), "=r"(v.z), "=r"(v.w) : "l"(p));
    return v;
}
__device__ __forceinline__ uint32_t ldg32(const void* p) {
    uint32_t v;
    asm volatile("ld.global.nc.L1::no_allocate.L2::256B.u32 %0, [%1];" : "=r"(v) : "l"(p));
    return v;
}
__device__ __forceinline__ void mma(float (&c)[4], uint32_t a0, uint32_t a1, uint32_t a2, uint32_t a3, uint32_t b0, uint32_t b1) {
    asm volatile("mma.sync.aligned.m16n8k16.row.col.f32.bf16.bf16.f32 {%0,%1,%2,%3}, {%4,%5,%6,%7}, {%8,%9}, {%0,%1,%2,%3};"
                 : "+f"(c[0]), "+f"(c[1]), "+f"(c[2]), "+f"(c[3])
                 : "r"(a0), "r"(a1), "r"(a2), "r"(a3), "r"(b0), "r"(b1));
}
__device__ __forceinline__ uint32_t lo2(uint32_t a, uint32_t b) { return __byte_perm(a, b, 0x5410); }
__device__ __forceinline__ uint32_t hi2(uint32_t a, uint32_t b) { return __byte_perm(a, b, 0x7632); }
__device__ __forceinline__ float bf_lo(uint32_t w) { return __uint_as_float(w << 16); }
__device__ __forceinline__ float bf_hi(uint32_t w) { return __uint_as_float(w & 0xffff0000u); }
__device__ __forceinline__ float rbf(float v) { return __bfloat162float(__float2bfloat16_rn(v)); }
__device__ __forceinline__ uint32_t pack2(float lo, float hi) {
    __nv_bfloat162 v = __floats2bfloat162_rn(lo, hi);
    return *reinterpret_cast<uint32_t*>(&v);
}

__device__ __forceinline__ void publish(uint4* p, float a, float b, float c, float d, uint32_t tag) {
    asm volatile("st.relaxed.gpu.global.v4.u32 [%0], {%1,%2,%3,%4};" :: "l"(p),
                 "r"((__float_as_uint(a) & ~3u) | tag), "r"((__float_as_uint(b) & ~3u) | tag),
                 "r"((__float_as_uint(c) & ~3u) | tag), "r"((__float_as_uint(d) & ~3u) | tag) : "memory");
}
__device__ __forceinline__ uint4 peek(const uint4* p) {
    uint4 v;
    asm volatile("ld.relaxed.gpu.global.v4.u32 {%0,%1,%2,%3}, [%4];" : "=r"(v.x), "=r"(v.y), "=r"(v.z), "=r"(v.w) : "l"(p) : "memory");
    return v;
}
__device__ __forceinline__ bool fresh(uint4 v, uint32_t tag) {
    return (((v.x ^ tag) | (v.y ^ tag) | (v.z ^ tag) | (v.w ^ tag)) & 3u) == 0;
}
__device__ __forceinline__ float untag(uint32_t w) { return __uint_as_float(w & ~3u); }
__device__ __forceinline__ uint4 wait_fresh(const uint4* p, uint32_t tag) {
    uint4 v = peek(p);
    for (int it = 0; !fresh(v, tag) && it < SPIN_LIMIT; it++) v = peek(p);
    return v;
}
__device__ __forceinline__ float reduce_scatter4(float a, float b, float c, float d, int lane) {
    const bool up = lane & 16;
    float k0 = (up ? c : a) + __shfl_xor_sync(~0u, up ? a : c, 16);
    float k1 = (up ? d : b) + __shfl_xor_sync(~0u, up ? b : d, 16);
    const bool odd = lane & 8;
    return (odd ? k1 : k0) + __shfl_xor_sync(~0u, odd ? k0 : k1, 8);
}

__device__ __forceinline__ void layernorm_row(uint4 r0, uint4 r1, uint32_t dst, int lane) {
    const uint32_t w[8] = {r0.x, r0.y, r0.z, r0.w, r1.x, r1.y, r1.z, r1.w};
    float v[16], s = 0.f;
#pragma unroll
    for (int i = 0; i < 8; i++) { v[2 * i] = bf_lo(w[i]); v[2 * i + 1] = bf_hi(w[i]); s += v[2 * i] + v[2 * i + 1]; }
#pragma unroll
    for (int o = 16; o; o >>= 1) s += __shfl_xor_sync(~0u, s, o);
    const float mean = s * (1.f / DM);
    float q = 0.f;
#pragma unroll
    for (int i = 0; i < 16; i++) q += (v[i] - mean) * (v[i] - mean);
#pragma unroll
    for (int o = 16; o; o >>= 1) q += __shfl_xor_sync(~0u, q, o);
    const float mb = rbf(mean);
    const float den = rbf(__fsqrt_rn(rbf(rbf(q * (1.f / DM)) + 1e-5f)));
    const float inv = __frcp_rn(den);
    uint32_t o[8];
#pragma unroll
    for (int i = 0; i < 8; i++) {
        const uint32_t d = pack2(v[2 * i] - mb, v[2 * i + 1] - mb);
        o[i] = pack2(bf_lo(d) * inv, bf_hi(d) * inv);
    }
    sts128(dst + lane * 16, make_uint4(o[0], o[1], o[2], o[3]));
    sts128(dst + 512 + lane * 16, make_uint4(o[4], o[5], o[6], o[7]));
}

__device__ __forceinline__ void gemv_step(float (&c)[4], const uint32_t (&r)[8], uint4 b) {
    mma(c, lo2(r[0], r[1]), hi2(r[0], r[1]), lo2(r[2], r[3]), hi2(r[2], r[3]), b.x, b.y);
    mma(c, lo2(r[4], r[5]), hi2(r[4], r[5]), lo2(r[6], r[7]), hi2(r[6], r[7]), b.z, b.w);
}
__device__ __forceinline__ void load_rows(uint32_t (&r)[8], const bf16* p, int stride) {
#pragma unroll
    for (int i = 0; i < 8; i++) r[i] = ldg32(p + i * stride);
}

struct Ring {
    uint32_t stage, phase;
    __device__ __forceinline__ void next() { if (++stage == STAGES) { stage = 0; phase ^= 1; } }
};
__device__ __forceinline__ void release(uint32_t sb, Ring& ring, int lane, uint32_t dep) {
    __syncwarp();
    if (lane == 0) mbar_arrive(sb + SM_EMPTY + ring.stage * 8 + (dep & blockIdx.y));
    ring.next();
}

__device__ __forceinline__ void producer(uint32_t sb, int h, int j, const bf16* kc, const bf16* vc, const bf16* wo,
                                         unsigned* progress) {
    uint64_t stream_pol, shared_pol;
    asm volatile("createpolicy.fractional.L2::evict_first.b64 %0, 1.0;" : "=l"(stream_pol));
    asm volatile("createpolicy.fractional.L2::evict_normal.b64 %0, 1.0;" : "=l"(shared_pol));
    Ring ring = {1 + DEPTH1, 1}, landed = {1, 0};
    int inflight = DEPTH1, issued = DEPTH1;
    unsigned total = 0;
    auto issue = [&](const char* src, uint64_t pol) {
        for (const int depth = issued < DEPTH_SWITCH ? DEPTH1 : DEPTH2; inflight >= depth; inflight--) {
            mbar_wait(sb + SM_FULL + landed.stage * 8, landed.phase);
            landed.next();
        }
        const int delay = min(((issued - DEPTH1) * NCTA - NCTA / 2 - (int)total) * PACE_GAIN, PACE_MAX);
        for (const uint32_t c0 = clock(); (int)(clock() - c0) < delay;) {}
        mbar_wait(sb + SM_EMPTY + ring.stage * 8, ring.phase);
        mbar_expect_tx(sb + SM_FULL + ring.stage * 8, TILE_BYTES);
        bulk_load(sb + ring.stage * TILE_BYTES, src, TILE_BYTES, sb + SM_FULL + ring.stage * 8, pol);
        if (PACE_GAIN) total = atomicAdd(progress, 1);
        ring.next();
        inflight++;
        issued++;
    };
#pragma unroll 1
    for (int seg = 0; seg < 4; seg++) {
        const char* src = (const char*)((seg & 1) ? vc : kc) + ((size_t)((2 * j + (seg >> 1)) * NH + h) << 20);
#pragma unroll 1
        for (int it = seg ? 0 : DEPTH1; it < TILES; it++) {
            issue(src + it * TILE_BYTES, stream_pol);
            if (seg == 0 && (it & 7) == 7) issue((const char*)wo + (size_t)(h * 4 + (it >> 3)) * TILE_BYTES, shared_pol);
        }
        if (seg & 1) mbar_arrive(sb + SM_LAST + (seg >> 1) * 8);
    }
    if (total == NCTA * (4 * TILES + 4 - DEPTH1) - 1) *progress = 0;
}

__device__ __forceinline__ void aux_warp(uint32_t sb, int h, int j, const bf16* x, const bf16* wg, const bf16* wu,
                                         const bf16* wd, bf16* out, Scratch* sc) {
    const int lane = threadIdx.x & 31, g = lane >> 2, t = lane & 3;
    asm volatile("bar.sync 2, 320;" ::: "memory");
    const uint32_t epoch = lds32(sb + SM_EPOCH), tag = (epoch + 1) & 3;
    if ((blockIdx.x & 7) != 7) {
        const int f0 = ((blockIdx.x >> 3) * 7 + (blockIdx.x & 7)) * 16 + 2 * g;
        float cg[4] = {}, cu[4] = {};
#pragma unroll 1
        for (int k = 8 * t; k < DM; k += 64) {
            uint32_t g0[8], g1[8], u0[8], u1[8];
            load_rows(g0, wg + k * FF + f0, FF);
            load_rows(u0, wu + k * FF + f0, FF);
            load_rows(g1, wg + (k + 32) * FF + f0, FF);
            load_rows(u1, wu + (k + 32) * FF + f0, FF);
            const uint4 b0 = lds128(sb + SM_XN + g * XN_STRIDE + k * 2), b1 = lds128(sb + SM_XN + g * XN_STRIDE + k * 2 + 64);
            gemv_step(cg, g0, b0);
            gemv_step(cu, u0, b0);
            gemv_step(cg, g1, b1);
            gemv_step(cu, u1, b1);
        }
        uint32_t hw[4];
#pragma unroll
        for (int e = 0; e < 4; e++) hw[e] = __float_as_uint(rbf(rbf(cg[e]) * rbf(cu[e]))) | tag;
        uint32_t* dst = (uint32_t*)sc->hx + 2 * t * FF + f0;
        asm volatile("st.relaxed.gpu.global.v2.u32 [%0], {%1,%2};" :: "l"(dst), "r"(hw[0]), "r"(hw[2]) : "memory");
        asm volatile("st.relaxed.gpu.global.v2.u32 [%0], {%1,%2};" :: "l"(dst + FF), "r"(hw[1]), "r"(hw[3]) : "memory");
    }
    PROF(lane == 0, 10);
    {
        float c[4] = {};
#pragma unroll 1
        for (int k = j * (FF / 4) + 8 * t; k < (j + 1) * (FF / 4); k += 64) {
            uint32_t r0[8], r1[8];
            load_rows(r0, wd + k * DM + h * 16 + 2 * g, DM);
            load_rows(r1, wd + (k + 32) * DM + h * 16 + 2 * g, DM);
            const uint4* hp = sc->hx + (g * FF + k) / 4;
            uint4 a0 = peek(hp), a1 = peek(hp + 1), a2 = peek(hp + 8), a3 = peek(hp + 9);
            for (int it = 0; !(fresh(a0, tag) && fresh(a1, tag) && fresh(a2, tag) && fresh(a3, tag)) && it < SPIN_LIMIT; it++) {
                __nanosleep(200);
                a0 = peek(hp); a1 = peek(hp + 1); a2 = peek(hp + 8); a3 = peek(hp + 9);
            }
            __syncwarp();
            gemv_step(c, r0, make_uint4(hi2(a0.x, a0.y), hi2(a0.z, a0.w), hi2(a1.x, a1.y), hi2(a1.z, a1.w)));
            gemv_step(c, r1, make_uint4(hi2(a2.x, a2.y), hi2(a2.z, a2.w), hi2(a3.x, a3.y), hi2(a3.z, a3.w)));
        }
        publish(sc->fx + ((t * 32 + h) * 4 + j) * 8 + g, c[0], c[1], c[2], c[3], tag);
    }
    const uint4 f = wait_fresh(sc->fx + (j * 32 + h) * 32 + lane, tag);
    __syncwarp();
    const float d = rbf(reduce_scatter4(untag(f.x), untag(f.y), untag(f.z), untag(f.w), lane));
    const float gate_all = rbf(d / (1.f + expf(-d)));
    PROF(lane == 0, 11);
    const int col = 4 * t + (lane >> 3);
#pragma unroll 1
    for (int pr = 0; pr < 2; pr++) {
        const int oidx = (2 * j + pr) * DM + h * 16 + col;
        const float xv = __bfloat162float(x[oidx]);
        const float gate = __shfl_sync(~0u, gate_all, ((col & 1) << 4) | (pr << 3) | (col >> 1));
        const uint4* sp = sc->sx + ((2 * j + pr) * 32 + h) * (NH * 4) + lane;
        mbar_wait(sb + SM_LAST + pr * 8, 0);
        uint4 v[4];
#pragma unroll
        for (int i = 0; i < 4; i++) v[i] = peek(sp + i * 32);
        for (int it = 0; it < SPIN_LIMIT; it++) {
            bool done = true;
#pragma unroll
            for (int i = 0; i < 4; i++)
                if (!fresh(v[i], tag)) { v[i] = peek(sp + i * 32); done = false; }
            if (done) break;
        }
        __syncwarp();
#define SUM4(f) ((untag(v[0].f) + untag(v[1].f)) + (untag(v[2].f) + untag(v[3].f)))
        float s = reduce_scatter4(SUM4(x), SUM4(y), SUM4(z), SUM4(w), lane);
#undef SUM4
        s += __shfl_xor_sync(~0u, s, 4);
        if (!(lane & 4)) out[oidx] = __float2bfloat16_rn(xv + rbf(rbf(s) * gate));
    }
    if (blockIdx.x == 0 && lane == 0) sc->epoch = epoch + 1;
    PROF(lane == 0, 9);
}

__device__ __forceinline__ void keep_wo_tile(uint32_t sb, Ring& ring, uint32_t (&lo)[4][4], uint32_t (&hi)[4][4]) {
    const int warp = threadIdx.x >> 5, lane = threadIdx.x & 31, g = lane >> 2, t = lane & 3;
    mbar_wait(sb + SM_FULL + ring.stage * 8, ring.phase);
    const uint32_t base = sb + ring.stage * TILE_BYTES + t * 8192 + warp * 128 + g * 16;
    uint4 r[8];
#pragma unroll
    for (int i = 0; i < 8; i++) r[i] = lds128(base + i * 1024);
#define WO_TILE(i, f) \
    lo[i][0] = lo2(r[0].f, r[1].f); lo[i][1] = hi2(r[0].f, r[1].f); lo[i][2] = lo2(r[2].f, r[3].f); lo[i][3] = hi2(r[2].f, r[3].f); \
    hi[i][0] = lo2(r[4].f, r[5].f); hi[i][1] = hi2(r[4].f, r[5].f); hi[i][2] = lo2(r[6].f, r[7].f); hi[i][3] = hi2(r[6].f, r[7].f);
    WO_TILE(0, x) WO_TILE(1, y) WO_TILE(2, z) WO_TILE(3, w)
#undef WO_TILE
    release(sb, ring, lane, lo[0][0] | lo[0][2] | hi[0][0] | hi[0][2]);
}

__device__ __forceinline__ void load_q(uint32_t sb, int pr, uint4 (&q)[4]) {
    const int lane = threadIdx.x & 31, g = lane >> 2, t = lane & 3;
#pragma unroll
    for (int j = 0; j < 4; j++) q[j] = lds128(sb + SM_Q + pr * (DH * 2) + (4 * (j ^ (g & 1)) + t) * 16);
}
__device__ __forceinline__ void load_k(uint32_t sb, const Ring& ring, uint4 (&k)[8]) {
    const int warp = threadIdx.x >> 5, lane = threadIdx.x & 31, g = lane >> 2, t = lane & 3;
    mbar_wait(sb + SM_FULL + ring.stage * 8, ring.phase);
    const uint32_t base = sb + ring.stage * TILE_BYTES + (warp * 16 + g) * 256 + t * 16, swap = (g & 1) * 64;
#pragma unroll
    for (int j = 0; j < 4; j++) {
        k[2 * j] = lds128(base + ((j * 64) ^ swap));
        k[2 * j + 1] = lds128(base + 2048 + ((j * 64) ^ swap));
    }
}
__device__ __forceinline__ uint32_t score_tile(uint32_t sb, int it, const uint4 (&k)[8], const uint4 (&q)[4]) {
    const int warp = threadIdx.x >> 5, lane = threadIdx.x & 31, g = lane >> 2, t = lane & 3;
    float c0[4] = {}, c1[4] = {};
#pragma unroll
    for (int j = 0; j < 4; j++) {
        mma(c0, k[2 * j].x, k[2 * j + 1].x, k[2 * j].y, k[2 * j + 1].y, q[j].x, q[j].y);
        mma(c1, k[2 * j].z, k[2 * j + 1].z, k[2 * j].w, k[2 * j + 1].w, q[j].z, q[j].w);
    }
    const float lo = (g & 1) ? c0[1] + c1[1] : c0[0] + c1[0];
    const float hi = (g & 1) ? c0[3] + c1[3] : c0[2] + c1[2];
    const float s = rbf((t & 1) ? hi : lo) * 0.08838834764831845f;
    if (t < 2) sts16(sb + SM_P + warp * 1024 + it * 32 + (g + 8 * t) * 2, __bfloat16_as_ushort(__float2bfloat16_rn(s)));
    return __float_as_uint(lo);
}
__device__ __forceinline__ void phase_qk(uint32_t sb, Ring& ring, int pr, uint32_t (&wof)[8][4][4]) {
    uint4 q[4];
    load_q(sb, pr, q);
#pragma unroll 1
    for (int it = pr ? 0 : NPRE; it < TILES; it++) {
        uint4 k[8];
        load_k(sb, ring, k);
        release(sb, ring, threadIdx.x & 31, score_tile(sb, it, k, q));
        if (pr == 0 && (it & 7) == 7) {
            switch (it >> 3) {
                case 0: keep_wo_tile(sb, ring, wof[0], wof[1]); break;
                case 1: keep_wo_tile(sb, ring, wof[2], wof[3]); break;
                case 2: keep_wo_tile(sb, ring, wof[4], wof[5]); break;
                default: keep_wo_tile(sb, ring, wof[6], wof[7]); break;
            }
        }
    }
}

__device__ __forceinline__ void phase_softmax(uint32_t sb) {
    const int warp = threadIdx.x >> 5, lane = threadIdx.x & 31;
    const uint32_t a = sb + SM_P + warp * 1024 + lane * 16;
    __syncwarp();
    const uint4 r0 = lds128(a), r1 = lds128(a + 512);
    const uint32_t w[8] = {r0.x, r0.y, r0.z, r0.w, r1.x, r1.y, r1.z, r1.w};
    float v[16], m = -INFINITY;
#pragma unroll
    for (int i = 0; i < 8; i++) { v[2 * i] = bf_lo(w[i]); v[2 * i + 1] = bf_hi(w[i]); m = fmaxf(m, fmaxf(v[2 * i], v[2 * i + 1])); }
#pragma unroll
    for (int o = 16; o; o >>= 1) m = fmaxf(m, __shfl_xor_sync(~0u, m, o));
    if (lane == 0) sts32(sb + SM_STAT + warp * 4, __float_as_uint(m));
    cons_sync();
    {
        const uint4 s0 = lds128(sb + SM_STAT), s1 = lds128(sb + SM_STAT + 16);
        m = fmaxf(fmaxf(fmaxf(__uint_as_float(s0.x), __uint_as_float(s0.y)), fmaxf(__uint_as_float(s0.z), __uint_as_float(s0.w))),
                  fmaxf(fmaxf(__uint_as_float(s1.x), __uint_as_float(s1.y)), fmaxf(__uint_as_float(s1.z), __uint_as_float(s1.w))));
    }
    float l = 0.f;
#pragma unroll
    for (int i = 0; i < 16; i++) { v[i] = expf(v[i] - m); l += v[i]; }
#pragma unroll
    for (int o = 16; o; o >>= 1) l += __shfl_xor_sync(~0u, l, o);
    if (lane == 0) sts32(sb + SM_STAT + 32 + warp * 4, __float_as_uint(l));
    cons_sync();
    {
        const uint4 s0 = lds128(sb + SM_STAT + 32), s1 = lds128(sb + SM_STAT + 48);
        l = ((__uint_as_float(s0.x) + __uint_as_float(s0.y)) + (__uint_as_float(s0.z) + __uint_as_float(s0.w))) +
            ((__uint_as_float(s1.x) + __uint_as_float(s1.y)) + (__uint_as_float(s1.z) + __uint_as_float(s1.w)));
    }
    const float inv = 1.f / l;
    uint32_t o[8];
#pragma unroll
    for (int i = 0; i < 8; i++) o[i] = pack2(v[2 * i] * inv, v[2 * i + 1] * inv);
    sts128(a, make_uint4(o[0], o[1], o[2], o[3]));
    sts128(a + 512, make_uint4(o[4], o[5], o[6], o[7]));
    __syncwarp();
}

__device__ __forceinline__ void phase_pv(uint32_t sb, Ring& ring) {
    const int tid = threadIdx.x, warp = tid >> 5, lane = tid & 31, g = lane >> 2, t = lane & 3;
    const uint32_t sel0 = g == 2 * t ? 0x4410 : g == 2 * t + 1 ? 0x1044 : 0x4444;
    const uint32_t sel1 = g == 2 * t ? 0x4432 : g == 2 * t + 1 ? 0x3244 : 0x4444;
    const uint32_t voff = warp * 4096 + lane * 16;
    uint32_t psrc = sb + SM_P + warp * 1024;
    float c0[4] = {}, c1[4] = {};
#pragma unroll 1
    for (int it = 0; it < TILES; it++) {
        const uint4 pa = lds128(psrc), pb = lds128(psrc + 16);
        psrc += 32;
        const uint32_t p[8] = {pa.x, pa.y, pa.z, pa.w, pb.x, pb.y, pb.z, pb.w};
        mbar_wait(sb + SM_FULL + ring.stage * 8, ring.phase);
        const uint32_t base = sb + ring.stage * TILE_BYTES + voff;
        uint4 v[8];
#pragma unroll
        for (int j = 0; j < 8; j++) v[j] = ldsm4(base + j * 512);
#pragma unroll
        for (int j = 0; j < 8; j += 2) {
            mma(c0, v[j].x, v[j].y, v[j].z, v[j].w, __byte_perm(p[j], 0, sel0), __byte_perm(p[j], 0, sel1));
            mma(c1, v[j + 1].x, v[j + 1].y, v[j + 1].z, v[j + 1].w, __byte_perm(p[j + 1], 0, sel0), __byte_perm(p[j + 1], 0, sel1));
        }
        release(sb, ring, lane, __float_as_uint(c0[0]) | __float_as_uint(c1[0]));
    }
    sts64f(sb + SM_RED + warp * 512 + lane * 8, c0[0] + c1[0], c0[1] + c1[1]);
    sts64f(sb + SM_RED + warp * 512 + 256 + lane * 8, c0[2] + c1[2], c0[3] + c1[3]);
    cons_sync();
    if (tid < 64) {
        float2 r[8];
#pragma unroll
        for (int w = 0; w < 8; w++) r[w] = lds64f(sb + SM_RED + w * 512 + tid * 8);
        sts32(sb + SM_O + tid * 4,
              pack2(((r[0].x + r[1].x) + (r[2].x + r[3].x)) + ((r[4].x + r[5].x) + (r[6].x + r[7].x)),
                    ((r[0].y + r[1].y) + (r[2].y + r[3].y)) + ((r[4].y + r[5].y) + (r[6].y + r[7].y))));
    }
    cons_sync();
}

__device__ __forceinline__ void consumer(uint32_t sb, int h, int j, const bf16* x, const bf16* wq, Scratch* sc) {
    const int tid = threadIdx.x, warp = tid >> 5, lane = tid & 31, g = lane >> 2, t = lane & 3;
    uint32_t tag;
    Ring ring = {0, 0};
    {
        const int r = tid >> 4;
        const bf16* wp = wq + (unsigned)((128 * j + r) * (NH * DH) + h * DH + (tid & 15) * 8);
        const uint32_t dst = sb + r * 256 + (((tid & 15) ^ (r & 1) ^ ((r >> 2) & 2)) << 4);
#pragma unroll
        for (int i = 0; i < 8; i++) cp_async16((dst ^ ((i & 1) << 6)) + i * 4096, wp + i * 16 * (NH * DH));
        const uint4 x0 = ldg128(x + warp * DM + lane * 8), x1 = ldg128(x + warp * DM + 256 + lane * 8);
        unsigned epoch;
        if (tid == 0) epoch = *(volatile unsigned*)&sc->epoch;
        PROF(tid == 0, 12);
        asm volatile("setmaxnreg.inc.sync.aligned.u32 208;");
        PROF(tid == 0 && x0.x != 0x12345, 13);
        layernorm_row(x0, x1, sb + SM_XN + warp * XN_STRIDE, lane);
        PROF(tid == 0, 14);
        if (tid == 0) sts32(sb + SM_EPOCH, epoch);
        asm volatile("cp.async.wait_all;" ::: "memory");
        asm volatile("bar.sync 2, 320;" ::: "memory");
        PROF(tid == 0, 1);
        tag = (lds32(sb + SM_EPOCH) + 1) & 3;
        const uint32_t a = sb + (4 * (lane & 6) + (lane & 1) + 2 * (lane >> 4)) * 256 + (((2 * warp + ((lane >> 3) & 1)) ^ (lane & 7)) << 4);
        float c0[4] = {}, c1[4] = {};
#pragma unroll
        for (int kk = 0; kk < 4; kk++) {
            const uint4 b = lds128(sb + SM_XN + g * XN_STRIDE + (128 * j + kk * 32 + 8 * t) * 2);
            const uint4 a0 = ldsm4t(a + kk * 8192), a1 = ldsm4t(a + kk * 8192 + 1024);
            mma(c0, a0.x, a0.y, a0.z, a0.w, b.x, b.y);
            mma(c1, a1.x, a1.y, a1.z, a1.w, b.z, b.w);
        }
        publish(sc->qx + ((h * 4 + t) * 4 + j) * 64 + warp * 8 + g, c0[0] + c1[0], c0[1] + c1[1], c0[2] + c1[2], c0[3] + c1[3], tag);
        release(sb, ring, lane, __float_as_uint(c0[0]) | __float_as_uint(c1[0]));
        PROF(tid == 0, 2);
        uint4 k[NPRE + 1][8];
#pragma unroll
        for (int n = 0; n < NPRE; n++) {
            load_k(sb, ring, k[n]);
            release(sb, ring, lane, k[n][0].x | k[n][1].x | k[n][2].x | k[n][3].x | k[n][4].x | k[n][5].x | k[n][6].x | k[n][7].x);
        }
        const int hg = lane >> 3, cp = lane & 7;
        const uint4 f = wait_fresh(sc->qx + ((h * 4 + j) * 4 + hg) * 64 + warp * 8 + cp, tag);
        __syncwarp();
        const float qv = reduce_scatter4(untag(f.x), untag(f.y), untag(f.z), untag(f.w), lane);
        sts16(sb + SM_Q + (hg & 1) * (DH * 2) + (warp * 16 + cp + 8 * (hg >> 1)) * 2, __bfloat16_as_ushort(__float2bfloat16_rn(qv)));
        cons_sync();
        PROF(tid == 0, 3);
        uint4 q[4];
        load_q(sb, 0, q);
#pragma unroll
        for (int n = 0; n < NPRE; n++) score_tile(sb, n, k[n], q);
    }

    uint32_t wof[8][4][4];
#pragma unroll
    for (int i = 0; i < 128; i++) asm volatile("" : "=r"(wof[i >> 4][(i >> 2) & 3][i & 3]));
#pragma unroll 1
    for (int pr = 0; pr < 2; pr++) {
        phase_qk(sb, ring, pr, wof);
        phase_softmax(sb);
        PROF(tid == 0, 4 + pr);
        phase_pv(sb, ring);
        PROF(tid == 0 && pr == 1, 6);
        float acc[4][4] = {};
#pragma unroll
        for (int kk = 0; kk < 4; kk++) {
            const uint4 b = lds128(sb + SM_O + (kk * 32 + 8 * t) * 2);
#pragma unroll
            for (int i = 0; i < 4; i++) mma(acc[i], wof[2 * kk][i][0], wof[2 * kk][i][1], wof[2 * kk][i][2], wof[2 * kk][i][3], b.x, b.y);
#pragma unroll
            for (int i = 0; i < 4; i++) mma(acc[i], wof[2 * kk + 1][i][0], wof[2 * kk + 1][i][1], wof[2 * kk + 1][i][2], wof[2 * kk + 1][i][3], b.z, b.w);
        }
        if (t < 2)
            publish(sc->sx + (((2 * j + pr) * 32 + warp * 4 + (g >> 1)) * NH + h) * 4 + (g & 1) * 2 + t,
                    t ? acc[2][0] : acc[0][0], t ? acc[2][2] : acc[0][2], t ? acc[3][0] : acc[1][0], t ? acc[3][2] : acc[1][2], tag);
        __syncwarp();
        PROF(tid == 0 && pr == 1, 7);
    }
}

__global__ void __launch_bounds__(NTHREADS, 1)
fused_decode_kernel(const bf16* __restrict__ x, const bf16* __restrict__ kc, const bf16* __restrict__ vc,
                    const bf16* __restrict__ wq, const bf16* __restrict__ wo, const bf16* __restrict__ wg,
                    const bf16* __restrict__ wu, const bf16* __restrict__ wd, bf16* __restrict__ out, Scratch* sc) {
    extern __shared__ __align__(128) unsigned char smem[];
    const uint32_t sb = (uint32_t)__cvta_generic_to_shared(smem);
    const int warp = threadIdx.x >> 5, lane = threadIdx.x & 31;
    const int h = blockIdx.x >> 2, j = blockIdx.x & 3;
    PROF(threadIdx.x == 256, 0);
    if (threadIdx.x == 256) {
        uint64_t pol;
        asm volatile("createpolicy.fractional.L2::evict_first.b64 %0, 1.0;" : "=l"(pol));
        const char* src = (const char*)kc + ((size_t)(2 * j * NH + h) << 20);
#pragma unroll
        for (int s = 1; s <= DEPTH1; s++) {
            mbar_init(sb + SM_FULL + s * 8, 1);
            asm volatile("fence.mbarrier_init.release.cluster;" ::: "memory");
            mbar_expect_tx(sb + SM_FULL + s * 8, TILE_BYTES);
            bulk_load(sb + s * TILE_BYTES, src + (s - 1) * TILE_BYTES, TILE_BYTES, sb + SM_FULL + s * 8, pol);
        }
    }
    PROF(threadIdx.x == 256, 15);
    if (warp >= 8) {
        asm volatile("setmaxnreg.dec.sync.aligned.u32 88;");
        if (warp == 8) {
            if (lane == 0) {
#pragma unroll
                for (int s = 0; s < STAGES; s++) {
                    if (s == 0 || s > DEPTH1) mbar_init(sb + SM_FULL + s * 8, 1);
                    mbar_init(sb + SM_EMPTY + s * 8, 8);
                }
                mbar_init(sb + SM_LAST, 1);
                mbar_init(sb + SM_LAST + 8, 1);
                asm volatile("fence.mbarrier_init.release.cluster;" ::: "memory");
                mbar_arrive(sb + SM_FULL);
            }
            __syncwarp();
            asm volatile("bar.arrive 2, 320;" ::: "memory");
            if (lane == 0) producer(sb, h, j, kc, vc, wo, &sc->progress);
            PROF(lane == 0, 8);
        } else if (warp == 9) {
            aux_warp(sb, h, j, x, wg, wu, wd, out, sc);
        }
    } else {
        consumer(sb, h, j, x, wq, sc);
    }
}

}

extern "C" void kernel_launch(void* const* d_in, const int* in_sizes, int n_in, void* d_out, int out_size) {
    static Scratch* scratch = nullptr;
    if (!scratch) {
        cudaFuncSetAttribute(fused_decode_kernel, cudaFuncAttributeMaxDynamicSharedMemorySize, SM_TOTAL);
        cudaGetSymbolAddress((void**)&scratch, g_scratch);
    }
    fused_decode_kernel<<<NCTA, NTHREADS, SM_TOTAL>>>(
        (const bf16*)d_in[0], (const bf16*)d_in[1], (const bf16*)d_in[2], (const bf16*)d_in[3], (const bf16*)d_in[4],
        (const bf16*)d_in[6], (const bf16*)d_in[7], (const bf16*)d_in[8], (bf16*)d_out, scratch);
}
```

```cpp
#include <cuda_runtime.h>
#include <cuda_bf16.h>
#include <stdint.h>

namespace {

typedef __nv_bfloat16 bf16;

constexpr int DM = 512, NH = 32, SK = 4096, DH = 128, FF = 1792;
constexpr int NCTA = 128, NTHREADS = 384;
constexpr int TILE_BYTES = 32768, STAGES = 6, TILES = SK * DH * 2 / TILE_BYTES;
constexpr int DEPTH1 = 2, DEPTH_SWITCH = 6, DEPTH2 = 3;
constexpr float PACE_BASE = 0.7f, PACE_GAIN = 2.5f, PACE_MAX = 1.5f;
constexpr int NPRE = 4;
constexpr int MID_AT = 24;

constexpr int XN_STRIDE = DM * 2 + 64;
constexpr int SM_P = STAGES * TILE_BYTES;
constexpr int SM_XN = SM_P + SK * 2;
constexpr int SM_RED = SM_XN + 8 * XN_STRIDE;
constexpr int SM_FIN = SM_RED + 8 * DH * 4;
constexpr int SM_Q = SM_FIN + 256 * 32;
constexpr int SM_O = SM_Q + 2 * DH * 2;
constexpr int SM_STAT = SM_O + DH * 2;
constexpr int SM_EPOCH = SM_STAT + 64;
constexpr int SM_FULL = SM_EPOCH + 16;
constexpr int SM_EMPTY = SM_FULL + STAGES * 8;
constexpr int SM_LAST = SM_EMPTY + STAGES * 8;
constexpr int SM_TOTAL = SM_LAST + 64;

struct __align__(256) Scratch {
    uint4 qx[NH * 4 * 4 * 64];
    uint4 hx[8 * FF / 4];
    uint4 fx[4 * 4 * 256];
    uint2 sx[8 * NH * 256];
    unsigned long long acc[8 * 2 * 256];
    unsigned epoch;
    unsigned pad[63];
    unsigned progress;
};
__device__ Scratch g_scratch;

__device__ __forceinline__ void mbar_init(uint32_t bar, uint32_t count) {
    asm volatile("mbarrier.init.shared::cta.b64 [%0], %1;" :: "r"(bar), "r"(count) : "memory");
}
__device__ __forceinline__ void mbar_expect_tx(uint32_t bar, uint32_t bytes) {
    asm volatile("mbarrier.arrive.expect_tx.shared::cta.b64 _, [%0], %1;" :: "r"(bar), "r"(bytes) : "memory");
}
__device__ __forceinline__ void mbar_arrive(uint32_t bar) {
    asm volatile("mbarrier.arrive.shared::cta.b64 _, [%0];" :: "r"(bar) : "memory");
}
template <int LIMIT = 1 << 16, typename F>
__device__ __forceinline__ void spin_until(F done) {
    int it = 0;
    while (!done() && ++it < LIMIT) {}
}
__device__ __forceinline__ void mbar_wait(uint32_t bar, uint32_t parity) {
    spin_until<1 << 14>([&] {
        uint32_t ok;
        asm volatile("{ .reg .pred p; mbarrier.try_wait.parity.shared::cta.b64 p, [%1], %2; selp.u32 %0, 1, 0, p; }"
                     : "=r"(ok) : "r"(bar), "r"(parity) : "memory");
        return ok != 0;
    });
}
__device__ __forceinline__ void bulk_load(uint32_t dst, const void* src, uint32_t bytes, uint32_t bar, uint64_t pol) {
    asm volatile("cp.async.bulk.shared::cluster.global.mbarrier::complete_tx::bytes.L2::cache_hint [%0], [%1], %2, [%3], %4;"
                 :: "r"(dst), "l"(src), "r"(bytes), "r"(bar), "l"(pol) : "memory");
}
__device__ __forceinline__ uint64_t stream_policy() {
    uint64_t pol;
    asm volatile("createpolicy.fractional.L2::evict_first.b64 %0, 1.0;" : "=l"(pol));
    return pol;
}
__device__ __forceinline__ int cons_tid() { return threadIdx.x - 128; }
__device__ __forceinline__ void cons_sync() { asm volatile("bar.sync 1, 256;" ::: "memory"); }

__device__ __forceinline__ uint4 lds128(uint32_t a) {
    uint4 v;
    asm volatile("ld.shared.v4.u32 {%0,%1,%2,%3}, [%4];" : "=r"(v.x), "=r"(v.y), "=r"(v.z), "=r"(v.w) : "r"(a) : "memory");
    return v;
}
__device__ __forceinline__ uint32_t lds32(uint32_t a) {
    uint32_t v;
    asm volatile("ld.shared.u32 %0, [%1];" : "=r"(v) : "r"(a) : "memory");
    return v;
}
__device__ __forceinline__ float2 lds64f(uint32_t a) {
    float2 v;
    asm volatile("ld.shared.v2.f32 {%0,%1}, [%2];" : "=f"(v.x), "=f"(v.y) : "r"(a) : "memory");
    return v;
}
__device__ __forceinline__ void sts128(uint32_t a, uint4 v) {
    asm volatile("st.shared.v4.u32 [%0], {%1,%2,%3,%4};" :: "r"(a), "r"(v.x), "r"(v.y), "r"(v.z), "r"(v.w) : "memory");
}
__device__ __forceinline__ void sts64f(uint32_t a, float x, float y) {
    asm volatile("st.shared.v2.f32 [%0], {%1,%2};" :: "r"(a), "f"(x), "f"(y) : "memory");
}
__device__ __forceinline__ void sts32(uint32_t a, uint32_t v) {
    asm volatile("st.shared.u32 [%0], %1;" :: "r"(a), "r"(v) : "memory");
}
__device__ __forceinline__ void sts16(uint32_t a, uint32_t v) {
    asm volatile("st.shared.u16 [%0], %1;" :: "r"(a), "h"((uint16_t)v) : "memory");
}
__device__ __forceinline__ uint4 ldsm4(uint32_t a) {
    uint4 v;
    asm volatile("ldmatrix.sync.aligned.m8n8.x4.shared.b16 {%0,%1,%2,%3}, [%4];"
                 : "=r"(v.x), "=r"(v.y), "=r"(v.z), "=r"(v.w) : "r"(a) : "memory");
    return v;
}
__device__ __forceinline__ uint4 ldsm4t(uint32_t a) {
    uint4 v;
    asm volatile("ldmatrix.sync.aligned.m8n8.x4.trans.shared.b16 {%0,%1,%2,%3}, [%4];"
                 : "=r"(v.x), "=r"(v.y), "=r"(v.z), "=r"(v.w) : "r"(a) : "memory");
    return v;
}
__device__ __forceinline__ void cp_async16(uint32_t dst, const void* src) {
    asm volatile("cp.async.cg.shared.global [%0], [%1], 16;" :: "r"(dst), "l"(src) : "memory");
}
__device__ __forceinline__ uint4 ldg128(const void* p) {
    uint4 v;
    asm volatile("ld.global.nc.L1::no_allocate.v4.u32 {%0,%1,%2,%3}, [%4];" : "=r"(v.x), "=r"(v.y), "=r"(v.z), "=r"(v.w) : "l"(p));
    return v;
}
__device__ __forceinline__ uint32_t ldg32(const void* p) {
    uint32_t v;
    asm volatile("ld.global.nc.L1::no_allocate.L2::128B.u32 %0, [%1];" : "=r"(v) : "l"(p));
    return v;
}
__device__ __forceinline__ void mma(float (&c)[4], uint32_t a0, uint32_t a1, uint32_t a2, uint32_t a3, uint32_t b0, uint32_t b1) {
    asm volatile("mma.sync.aligned.m16n8k16.row.col.f32.bf16.bf16.f32 {%0,%1,%2,%3}, {%4,%5,%6,%7}, {%8,%9}, {%0,%1,%2,%3};"
                 : "+f"(c[0]), "+f"(c[1]), "+f"(c[2]), "+f"(c[3])
                 : "r"(a0), "r"(a1), "r"(a2), "r"(a3), "r"(b0), "r"(b1));
}
__device__ __forceinline__ uint32_t lo2(uint32_t a, uint32_t b) { return __byte_perm(a, b, 0x5410); }
__device__ __forceinline__ uint32_t hi2(uint32_t a, uint32_t b) { return __byte_perm(a, b, 0x7632); }
__device__ __forceinline__ float bf_lo(uint32_t w) { return __uint_as_float(w << 16); }
__device__ __forceinline__ float bf_hi(uint32_t w) { return __uint_as_float(w & 0xffff0000u); }
__device__ __forceinline__ float rbf(float v) { return __bfloat162float(__float2bfloat16_rn(v)); }
__device__ __forceinline__ uint32_t pack2(float lo, float hi) {
    __nv_bfloat162 v = __floats2bfloat162_rn(lo, hi);
    return *reinterpret_cast<uint32_t*>(&v);
}

__device__ __forceinline__ void publish(uint4* p, float a, float b, float c, float d, uint32_t tag) {
    asm volatile("st.relaxed.gpu.global.v4.u32 [%0], {%1,%2,%3,%4};" :: "l"(p),
                 "r"((__float_as_uint(a) & ~3u) | tag), "r"((__float_as_uint(b) & ~3u) | tag),
                 "r"((__float_as_uint(c) & ~3u) | tag), "r"((__float_as_uint(d) & ~3u) | tag) : "memory");
}
__device__ __forceinline__ uint4 peek(const uint4* p) {
    uint4 v;
    asm volatile("ld.relaxed.gpu.global.v4.u32 {%0,%1,%2,%3}, [%4];" : "=r"(v.x), "=r"(v.y), "=r"(v.z), "=r"(v.w) : "l"(p) : "memory");
    return v;
}
__device__ __forceinline__ bool fresh(uint4 v, uint32_t tag) {
    return (((v.x ^ tag) | (v.y ^ tag) | (v.z ^ tag) | (v.w ^ tag)) & 3u) == 0;
}
__device__ __forceinline__ float untag(uint32_t w) { return __uint_as_float(w & ~3u); }
__device__ __forceinline__ uint4 wait_fresh(const uint4* p, uint32_t tag) {
    uint4 v;
    spin_until([&] { v = peek(p); return fresh(v, tag); });
    return v;
}
__device__ __forceinline__ float reduce_scatter4(float a, float b, float c, float d, int lane) {
    const bool up = lane & 16;
    float k0 = (up ? c : a) + __shfl_xor_sync(~0u, up ? a : c, 16);
    float k1 = (up ? d : b) + __shfl_xor_sync(~0u, up ? b : d, 16);
    const bool odd = lane & 8;
    return (odd ? k1 : k0) + __shfl_xor_sync(~0u, odd ? k0 : k1, 8);
}

__device__ __forceinline__ void layernorm_row(uint4 r0, uint4 r1, uint32_t dst, int lane) {
    const uint32_t w[8] = {r0.x, r0.y, r0.z, r0.w, r1.x, r1.y, r1.z, r1.w};
    float v[16], s = 0.f;
#pragma unroll
    for (int i = 0; i < 8; i++) { v[2 * i] = bf_lo(w[i]); v[2 * i + 1] = bf_hi(w[i]); s += v[2 * i] + v[2 * i + 1]; }
#pragma unroll
    for (int o = 16; o; o >>= 1) s += __shfl_xor_sync(~0u, s, o);
    const float mean = s * (1.f / DM);
    float q = 0.f;
#pragma unroll
    for (int i = 0; i < 16; i++) q += (v[i] - mean) * (v[i] - mean);
#pragma unroll
    for (int o = 16; o; o >>= 1) q += __shfl_xor_sync(~0u, q, o);
    const float mb = rbf(mean);
    const float den = rbf(__fsqrt_rn(rbf(rbf(q * (1.f / DM)) + 1e-5f)));
    const float inv = __frcp_rn(den);
    uint32_t o[8];
#pragma unroll
    for (int i = 0; i < 8; i++) {
        const uint32_t d = pack2(v[2 * i] - mb, v[2 * i + 1] - mb);
        o[i] = pack2(bf_lo(d) * inv, bf_hi(d) * inv);
    }
    sts128(dst + lane * 16, make_uint4(o[0], o[1], o[2], o[3]));
    sts128(dst + 512 + lane * 16, make_uint4(o[4], o[5], o[6], o[7]));
}

__device__ __forceinline__ void gemv_step(float (&c)[4], const uint32_t (&r)[8], uint4 b) {
    mma(c, lo2(r[0], r[1]), hi2(r[0], r[1]), lo2(r[2], r[3]), hi2(r[2], r[3]), b.x, b.y);
    mma(c, lo2(r[4], r[5]), hi2(r[4], r[5]), lo2(r[6], r[7]), hi2(r[6], r[7]), b.z, b.w);
}
__device__ __forceinline__ void load_rows(uint32_t (&r)[8], const bf16* p, int stride) {
#pragma unroll
    for (int i = 0; i < 8; i++) r[i] = ldg32(p + i * stride);
}

__device__ __forceinline__ int batch_of(int j, int i) { return j + 4 * i; }
__device__ __forceinline__ const char* cache_of(const bf16* cache, int h, int j, int i) {
    return (const char*)cache + ((size_t)(batch_of(j, i) * NH + h) << 20);
}

struct Ring {
    uint32_t stage, phase;
    __device__ __forceinline__ void next() { if (++stage == STAGES) { stage = 0; phase ^= 1; } }
};
__device__ __forceinline__ void release(uint32_t sb, Ring& ring, int lane, uint32_t dep) {
    __syncwarp();
    if (lane == 0) mbar_arrive(sb + SM_EMPTY + ring.stage * 8 + (dep & blockIdx.y));
    ring.next();
}

__device__ __forceinline__ void producer(uint32_t sb, int h, int j, const bf16* kc, const bf16* vc, const bf16* wo,
                                         Scratch* sc) {
    const uint64_t pol = stream_policy();
    Ring ring = {1 + DEPTH1, 1}, landed = {1, 0};
    int inflight = DEPTH1, counted = 0;
    const uint32_t t_start = clock();
    uint32_t t_prev = t_start;
    unsigned total = 0;
    auto acquire = [&](int depth) {
        for (; inflight >= depth; inflight--) {
            mbar_wait(sb + SM_FULL + landed.stage * 8, landed.phase);
            landed.next();
        }
        mbar_wait(sb + SM_EMPTY + ring.stage * 8, ring.phase);
    };
    auto pace = [&] {
        const float lead = (float)(counted * NCTA - NCTA / 2 - (int)total);
        const float per = __fdividef((float)(t_prev - t_start), (float)(total + DEPTH1 * NCTA));
        const int gap = (int)fminf(per * fminf(PACE_BASE * NCTA + PACE_GAIN * lead, PACE_MAX * NCTA), 8192.f);
        acquire(counted < DEPTH_SWITCH ? DEPTH1 : DEPTH2);
        while ((int)(clock() - t_prev) < gap) {}
    };
    auto issue = [&](const char* src) {
        mbar_expect_tx(sb + SM_FULL + ring.stage * 8, TILE_BYTES);
        bulk_load(sb + ring.stage * TILE_BYTES, src, TILE_BYTES, sb + SM_FULL + ring.stage * 8, pol);
        ring.next();
        inflight++;
    };
#pragma unroll 1
    for (int seg = 0; seg < 4; seg++) {
        const char* src = cache_of((seg & 1) ? vc : kc, h, j, seg >> 1);
#pragma unroll 1
        for (int it = seg ? 0 : DEPTH1; it < TILES - (seg == 3); it++) {
            pace();
            issue(src + it * TILE_BYTES);
            t_prev = clock();
            total = atomicAdd(&sc->progress, 1);
            counted++;
            if (seg == 0 && (it & 7) == 7) {
                acquire(STAGES);
                issue((const char*)wo + (size_t)(h * 4 + (it >> 3)) * TILE_BYTES);
            }
        }
    }
    pace();
    const char* src = cache_of(vc, h, j, 1) + (TILES - 1) * TILE_BYTES;
#pragma unroll 1
    for (int w = 0; w < 8; w++) {
        mbar_expect_tx(sb + SM_LAST + w * 8, TILE_BYTES / 8);
        bulk_load(sb + ring.stage * TILE_BYTES + w * (TILE_BYTES / 8), src + w * (TILE_BYTES / 8), TILE_BYTES / 8,
                  sb + SM_LAST + w * 8, pol);
    }
    if (total == NCTA * (4 * TILES - 1 - DEPTH1) - 1) {
        sc->progress = 0;
        sc->epoch = lds32(sb + SM_EPOCH) + 1;
    }
}

__device__ __forceinline__ void glu_warp(uint32_t sb, int h, int j, const bf16* wg, const bf16* wu, const bf16* wd, Scratch* sc) {
    const int lane = threadIdx.x & 31, g = lane >> 2, t = lane & 3;
    asm volatile("bar.sync 2, 320;" ::: "memory");
    const uint32_t tag = (lds32(sb + SM_EPOCH) + 1) & 3;
    if ((blockIdx.x & 7) != 7) {
        const int f0 = ((blockIdx.x >> 3) * 7 + (blockIdx.x & 7)) * 16 + 2 * g;
        float cg[4] = {}, cu[4] = {};
#pragma unroll 1
        for (int k = 8 * t; k < DM; k += 64) {
            uint32_t g0[8], g1[8], u0[8], u1[8];
            load_rows(g0, wg + k * FF + f0, FF);
            load_rows(u0, wu + k * FF + f0, FF);
            load_rows(g1, wg + (k + 32) * FF + f0, FF);
            load_rows(u1, wu + (k + 32) * FF + f0, FF);
            const uint4 b0 = lds128(sb + SM_XN + g * XN_STRIDE + k * 2), b1 = lds128(sb + SM_XN + g * XN_STRIDE + k * 2 + 64);
            gemv_step(cg, g0, b0);
            gemv_step(cu, u0, b0);
            gemv_step(cg, g1, b1);
            gemv_step(cu, u1, b1);
        }
        uint32_t hw[4];
#pragma unroll
        for (int e = 0; e < 4; e++) hw[e] = __float_as_uint(rbf(rbf(cg[e]) * rbf(cu[e]))) | tag;
        uint32_t* dst = (uint32_t*)sc->hx + 2 * t * FF + f0;
        asm volatile("st.relaxed.gpu.global.v2.u32 [%0], {%1,%2};" :: "l"(dst), "r"(hw[0]), "r"(hw[2]) : "memory");
        asm volatile("st.relaxed.gpu.global.v2.u32 [%0], {%1,%2};" :: "l"(dst + FF), "r"(hw[1]), "r"(hw[3]) : "memory");
    }
    {
        float c[4] = {};
#pragma unroll 1
        for (int k = j * (FF / 4) + 8 * t; k < (j + 1) * (FF / 4); k += 64) {
            uint32_t r0[8], r1[8];
            load_rows(r0, wd + k * DM + h * 16 + 2 * g, DM);
            load_rows(r1, wd + (k + 32) * DM + h * 16 + 2 * g, DM);
            const uint4* hp = sc->hx + (g * FF + k) / 4;
            uint4 a0, a1, a2, a3;
            spin_until([&] {
                a0 = peek(hp); a1 = peek(hp + 1); a2 = peek(hp + 8); a3 = peek(hp + 9);
                return fresh(a0, tag) && fresh(a1, tag) && fresh(a2, tag) && fresh(a3, tag);
            });
            __syncwarp();
            gemv_step(c, r0, make_uint4(hi2(a0.x, a0.y), hi2(a0.z, a0.w), hi2(a1.x, a1.y), hi2(a1.z, a1.w)));
            gemv_step(c, r1, make_uint4(hi2(a2.x, a2.y), hi2(a2.z, a2.w), hi2(a3.x, a3.y), hi2(a3.z, a3.w)));
        }
        publish(sc->fx + (t * 4 + j) * 256 + h * 8 + g, c[0], c[1], c[2], c[3], tag);
    }
}

__device__ __forceinline__ void keep_wo_tile(uint32_t sb, Ring& ring, uint32_t (&lo)[4][4], uint32_t (&hi)[4][4]) {
    const int warp = cons_tid() >> 5, lane = threadIdx.x & 31, g = lane >> 2, t = lane & 3;
    mbar_wait(sb + SM_FULL + ring.stage * 8, ring.phase);
    const uint32_t base = sb + ring.stage * TILE_BYTES + t * 8192 + warp * 128 + g * 16;
    uint4 r[8];
#pragma unroll
    for (int i = 0; i < 8; i++) r[i] = lds128(base + i * 1024);
#define WO_TILE(i, f) \
    lo[i][0] = lo2(r[0].f, r[1].f); lo[i][1] = hi2(r[0].f, r[1].f); lo[i][2] = lo2(r[2].f, r[3].f); lo[i][3] = hi2(r[2].f, r[3].f); \
    hi[i][0] = lo2(r[4].f, r[5].f); hi[i][1] = hi2(r[4].f, r[5].f); hi[i][2] = lo2(r[6].f, r[7].f); hi[i][3] = hi2(r[6].f, r[7].f);
    WO_TILE(0, x) WO_TILE(1, y) WO_TILE(2, z) WO_TILE(3, w)
#undef WO_TILE
    release(sb, ring, lane, lo[0][0] | lo[0][2] | hi[0][0] | hi[0][2]);
}

__device__ __forceinline__ void load_q(uint32_t sb, int pr, uint4 (&q)[4]) {
    const int lane = threadIdx.x & 31, g = lane >> 2, t = lane & 3;
#pragma unroll
    for (int j = 0; j < 4; j++) q[j] = lds128(sb + SM_Q + pr * (DH * 2) + (4 * (j ^ (g & 1)) + t) * 16);
}
__device__ __forceinline__ void load_k(uint32_t sb, const Ring& ring, uint4 (&k)[8]) {
    const int warp = cons_tid() >> 5, lane = threadIdx.x & 31, g = lane >> 2, t = lane & 3;
    mbar_wait(sb + SM_FULL + ring.stage * 8, ring.phase);
    const uint32_t base = sb + ring.stage * TILE_BYTES + (warp * 16 + g) * 256 + t * 16, swap = (g & 1) * 64;
#pragma unroll
    for (int j = 0; j < 4; j++) {
        k[2 * j] = lds128(base + ((j * 64) ^ swap));
        k[2 * j + 1] = lds128(base + 2048 + ((j * 64) ^ swap));
    }
}
__device__ __forceinline__ uint32_t score_tile(uint32_t sb, int it, const uint4 (&k)[8], const uint4 (&q)[4]) {
    const int warp = cons_tid() >> 5, lane = threadIdx.x & 31, g = lane >> 2, t = lane & 3;
    float c0[4] = {}, c1[4] = {};
#pragma unroll
    for (int j = 0; j < 4; j++) {
        mma(c0, k[2 * j].x, k[2 * j + 1].x, k[2 * j].y, k[2 * j + 1].y, q[j].x, q[j].y);
        mma(c1, k[2 * j].z, k[2 * j + 1].z, k[2 * j].w, k[2 * j + 1].w, q[j].z, q[j].w);
    }
    const float lo = (g & 1) ? c0[1] + c1[1] : c0[0] + c1[0];
    const float hi = (g & 1) ? c0[3] + c1[3] : c0[2] + c1[2];
    const float s = rbf((t & 1) ? hi : lo) * 0.08838834764831845f;
    if (t < 2) sts16(sb + SM_P + warp * 1024 + it * 32 + (g + 8 * t) * 2, __bfloat16_as_ushort(__float2bfloat16_rn(s)));
    return __float_as_uint(lo);
}
__device__ __forceinline__ void phase_qk(uint32_t sb, Ring& ring, int pr, uint32_t (&wof)[8][4][4]) {
    uint4 q[4];
    load_q(sb, pr, q);
#pragma unroll 1
    for (int it = pr ? 0 : NPRE; it < TILES; it++) {
        uint4 k[8];
        load_k(sb, ring, k);
        release(sb, ring, threadIdx.x & 31, score_tile(sb, it, k, q));
        if (pr == 0 && (it & 7) == 7) {
            switch (it >> 3) {
                case 0: keep_wo_tile(sb, ring, wof[0], wof[1]); break;
                case 1: keep_wo_tile(sb, ring, wof[2], wof[3]); break;
                case 2: keep_wo_tile(sb, ring, wof[4], wof[5]); break;
                default: keep_wo_tile(sb, ring, wof[6], wof[7]); break;
            }
        }
    }
}

__device__ __forceinline__ void phase_softmax(uint32_t sb) {
    const int warp = cons_tid() >> 5, lane = threadIdx.x & 31;
    const uint32_t a = sb + SM_P + warp * 1024 + lane * 16;
    __syncwarp();
    const uint4 r0 = lds128(a), r1 = lds128(a + 512);
    const uint32_t w[8] = {r0.x, r0.y, r0.z, r0.w, r1.x, r1.y, r1.z, r1.w};
    float v[16], m = -INFINITY;
#pragma unroll
    for (int i = 0; i < 8; i++) { v[2 * i] = bf_lo(w[i]); v[2 * i + 1] = bf_hi(w[i]); m = fmaxf(m, fmaxf(v[2 * i], v[2 * i + 1])); }
#pragma unroll
    for (int o = 16; o; o >>= 1) m = fmaxf(m, __shfl_xor_sync(~0u, m, o));
    if (lane == 0) sts32(sb + SM_STAT + warp * 4, __float_as_uint(m));
    cons_sync();
    {
        const uint4 s0 = lds128(sb + SM_STAT), s1 = lds128(sb + SM_STAT + 16);
        m = fmaxf(fmaxf(fmaxf(__uint_as_float(s0.x), __uint_as_float(s0.y)), fmaxf(__uint_as_float(s0.z), __uint_as_float(s0.w))),
                  fmaxf(fmaxf(__uint_as_float(s1.x), __uint_as_float(s1.y)), fmaxf(__uint_as_float(s1.z), __uint_as_float(s1.w))));
    }
    float l = 0.f;
#pragma unroll
    for (int i = 0; i < 16; i++) { v[i] = expf(v[i] - m); l += v[i]; }
#pragma unroll
    for (int o = 16; o; o >>= 1) l += __shfl_xor_sync(~0u, l, o);
    if (lane == 0) sts32(sb + SM_STAT + 32 + warp * 4, __float_as_uint(l));
    cons_sync();
    {
        const uint4 s0 = lds128(sb + SM_STAT + 32), s1 = lds128(sb + SM_STAT + 48);
        l = ((__uint_as_float(s0.x) + __uint_as_float(s0.y)) + (__uint_as_float(s0.z) + __uint_as_float(s0.w))) +
            ((__uint_as_float(s1.x) + __uint_as_float(s1.y)) + (__uint_as_float(s1.z) + __uint_as_float(s1.w)));
    }
    const float inv = 1.f / l;
    uint32_t o[8];
#pragma unroll
    for (int i = 0; i < 8; i++) o[i] = pack2(v[2 * i] * inv, v[2 * i + 1] * inv);
    sts128(a, make_uint4(o[0], o[1], o[2], o[3]));
    sts128(a + 512, make_uint4(o[4], o[5], o[6], o[7]));
    __syncwarp();
}

__device__ __forceinline__ uint32_t prmt_now(uint32_t a, uint32_t sel) {
    uint32_t d;
    asm volatile("prmt.b32 %0, %1, 0, %2;" : "=r"(d) : "r"(a), "r"(sel) : "memory");
    return d;
}
template <typename F>
__device__ __forceinline__ void phase_pv(uint32_t sb, Ring& ring, int pr, F midway) {
    const int tid = cons_tid(), warp = tid >> 5, lane = tid & 31, g = lane >> 2, t = lane & 3;
    const uint32_t sel0 = g == 2 * t ? 0x4410 : g == 2 * t + 1 ? 0x1044 : 0x4444;
    const uint32_t sel1 = g == 2 * t ? 0x4432 : g == 2 * t + 1 ? 0x3244 : 0x4444;
    uint32_t psrc = sb + SM_P + warp * 1024;
    float c0[4] = {}, c1[4] = {};
    auto tile = [&](uint32_t bar, uint32_t parity) {
        const uint4 pa = lds128(psrc), pb = lds128(psrc + 16);
        psrc += 32;
        const uint32_t p[8] = {pa.x, pa.y, pa.z, pa.w, pb.x, pb.y, pb.z, pb.w};
        uint32_t b0[8], b1[8];
#pragma unroll
        for (int j = 0; j < 8; j++) { b0[j] = prmt_now(p[j], sel0); b1[j] = prmt_now(p[j], sel1); }
        const uint32_t base = sb + ring.stage * TILE_BYTES + warp * 4096 + lane * 16;
        mbar_wait(bar, parity);
        uint4 v[8];
#pragma unroll
        for (int j = 0; j < 8; j++) v[j] = ldsm4(base + j * 512);
#pragma unroll
        for (int j = 0; j < 8; j += 2) {
            mma(c0, v[j].x, v[j].y, v[j].z, v[j].w, b0[j], b1[j]);
            mma(c1, v[j + 1].x, v[j + 1].y, v[j + 1].z, v[j + 1].w, b0[j + 1], b1[j + 1]);
        }
    };
#pragma unroll 1
    for (int it = 0; it < TILES - 1; it++) {
        tile(sb + SM_FULL + ring.stage * 8, ring.phase);
        release(sb, ring, lane, __float_as_uint(c0[0]) | __float_as_uint(c1[0]));
        if (it == MID_AT) midway();
    }
    tile(pr ? sb + SM_LAST + warp * 8 : sb + SM_FULL + ring.stage * 8, pr ? 0 : ring.phase);
    sts64f(sb + SM_RED + warp * 512 + lane * 8, c0[0] + c1[0], c0[1] + c1[1]);
    sts64f(sb + SM_RED + warp * 512 + 256 + lane * 8, c0[2] + c1[2], c0[3] + c1[3]);
    cons_sync();
    if (tid == 64) asm volatile("mbarrier.arrive.shared::cta.b64 _, [%0], 8;" :: "r"(sb + SM_EMPTY + ring.stage * 8) : "memory");
    ring.next();
    if (tid < 64) {
        float2 r[8];
#pragma unroll
        for (int w = 0; w < 8; w++) r[w] = lds64f(sb + SM_RED + w * 512 + tid * 8);
        sts32(sb + SM_O + tid * 4,
              pack2(((r[0].x + r[1].x) + (r[2].x + r[3].x)) + ((r[4].x + r[5].x) + (r[6].x + r[7].x)),
                    ((r[0].y + r[1].y) + (r[2].y + r[3].y)) + ((r[4].y + r[5].y) + (r[6].y + r[7].y))));
    }
    cons_sync();
}

__device__ __forceinline__ unsigned long long to_fixed(float v) {
    const bool ok = fabsf(v) < 256.f;
    return ((unsigned long long)__float2ll_rn(ok ? v * 0x1p38f : 0.f) << 12) | (ok ? 1 : 65);
}
__device__ __forceinline__ float from_fixed(uint32_t lo, uint32_t hi) {
    return fmaf(__uint2float_rn(lo & ~0xfffu), 0x1p-50f, __int2float_rn((int)hi) * 0x1p-18f);
}
__device__ __forceinline__ bool needs_fp32(uint32_t lo, float s) { return ((lo & 0xfc0) != 0) | (fabsf(s) < 0x1p-20f); }
__device__ __forceinline__ uint32_t combine(float s0, float s1, uint32_t gw, uint32_t xw) {
    const uint32_t sw = pack2(s0, s1);
    const uint32_t mw = pack2(bf_lo(sw) * bf_lo(gw), bf_hi(sw) * bf_hi(gw));
    return pack2(bf_lo(xw) + bf_lo(mw), bf_hi(xw) + bf_hi(mw));
}
__device__ __noinline__ float2 sum_fp32(const uint2* parts, uint32_t tag) {
    float2 s = make_float2(0.f, 0.f);
#pragma unroll 1
    for (int i = 0; i < NH; i += 16) {
        uint2 w[16];
        spin_until([&] {
            uint32_t stale = 0;
#pragma unroll
            for (int k = 0; k < 16; k++)
                asm volatile("ld.relaxed.gpu.global.v2.u32 {%0,%1}, [%2];" : "=r"(w[k].x), "=r"(w[k].y) : "l"(parts + (i + k) * 256) : "memory");
#pragma unroll
            for (int k = 0; k < 16; k++) stale |= (w[k].x ^ tag) | (w[k].y ^ tag);
            return (stale & 3) == 0;
        });
#pragma unroll
        for (int k = 0; k < 16; k++) { s.x += untag(w[k].x); s.y += untag(w[k].y); }
    }
    return s;
}
__device__ __forceinline__ void st_out(uint64_t p, uint32_t v) {
    asm volatile("st.global.u16 [%0], %1;" :: "l"(p), "h"((uint16_t)v) : "memory");
}
__device__ __forceinline__ float silu(float d) { return d / (1.f + expf(-d)); }

__device__ __forceinline__ void consumer(uint32_t sb, int h, int j, const bf16* x, const bf16* wq, bf16* out, Scratch* sc) {
    const int tid = cons_tid(), warp = tid >> 5, lane = tid & 31, g = lane >> 2, t = lane & 3;
    uint32_t tag;
    Ring ring = {0, 0};
    {
        const int r = tid >> 4;
        const bf16* wp = wq + (unsigned)((128 * j + r) * (NH * DH) + h * DH + (tid & 15) * 8);
        const uint32_t dst = sb + r * 256 + (((tid & 15) ^ (r & 1) ^ ((r >> 2) & 2)) << 4);
#pragma unroll
        for (int i = 0; i < 8; i++) cp_async16((dst ^ ((i & 1) << 6)) + i * 4096, wp + i * 16 * (NH * DH));
        const bf16* xp = x + batch_of(warp >> 1, warp & 1) * DM + lane * 8;
        const uint4 x0 = ldg128(xp), x1 = ldg128(xp + 256);
        unsigned epoch;
        if (tid == 0) epoch = *(volatile unsigned*)&sc->epoch;
        asm volatile("setmaxnreg.inc.sync.aligned.u32 208;");
        layernorm_row(x0, x1, sb + SM_XN + warp * XN_STRIDE, lane);
        if (tid == 0) sts32(sb + SM_EPOCH, epoch);
        asm volatile("cp.async.wait_all;" ::: "memory");
        asm volatile("fence.proxy.async.shared::cta;" ::: "memory");
        asm volatile("bar.sync 2, 320;" ::: "memory");
        tag = (lds32(sb + SM_EPOCH) + 1) & 3;
        const uint32_t a = sb + (4 * (lane & 6) + (lane & 1) + 2 * (lane >> 4)) * 256 + (((2 * warp + ((lane >> 3) & 1)) ^ (lane & 7)) << 4);
        float c0[4] = {}, c1[4] = {};
#pragma unroll
        for (int kk = 0; kk < 4; kk++) {
            const uint4 b = lds128(sb + SM_XN + g * XN_STRIDE + (128 * j + kk * 32 + 8 * t) * 2);
            const uint4 a0 = ldsm4t(a + kk * 8192), a1 = ldsm4t(a + kk * 8192 + 1024);
            mma(c0, a0.x, a0.y, a0.z, a0.w, b.x, b.y);
            mma(c1, a1.x, a1.y, a1.z, a1.w, b.z, b.w);
        }
        publish(sc->qx + ((h * 4 + t) * 4 + j) * 64 + warp * 8 + g, c0[0] + c1[0], c0[1] + c1[1], c0[2] + c1[2], c0[3] + c1[3], tag);
        release(sb, ring, lane, __float_as_uint(c0[0]) | __float_as_uint(c1[0]));
        uint4 k[NPRE][8];
#pragma unroll
        for (int n = 0; n < NPRE; n++) {
            load_k(sb, ring, k[n]);
            release(sb, ring, lane, k[n][0].x | k[n][1].x | k[n][2].x | k[n][3].x | k[n][4].x | k[n][5].x | k[n][6].x | k[n][7].x);
        }
        const int hg = lane >> 3, cp = lane & 7;
        const uint4 f = wait_fresh(sc->qx + ((h * 4 + j) * 4 + hg) * 64 + warp * 8 + cp, tag);
        __syncwarp();
        const float qv = reduce_scatter4(untag(f.x), untag(f.y), untag(f.z), untag(f.w), lane);
        sts16(sb + SM_Q + (hg & 1) * (DH * 2) + (warp * 16 + cp + 8 * (hg >> 1)) * 2, __bfloat16_as_ushort(__float2bfloat16_rn(qv)));
        cons_sync();
        uint4 q[4];
        load_q(sb, 0, q);
#pragma unroll
        for (int n = 0; n < NPRE; n++) score_tile(sb, n, k[n], q);
    }

    uint32_t wof[8][4][4], gate1;
#pragma unroll
    for (int i = 0; i < 128; i++) asm volatile("" : "=r"(wof[i >> 4][(i >> 2) & 3][i & 3]));
    asm volatile("" : "=r"(gate1));
#pragma unroll 1
    for (int pr = 0; pr < 2; pr++) {
        phase_qk(sb, ring, pr, wof);
        phase_softmax(sb);
        phase_pv(sb, ring, pr, [&] {
            const int b = batch_of(j, pr);
            const uint32_t xw = ((const uint32_t*)x)[b * 256 + tid];
            uint32_t gw = gate1;
            if (pr == 0) {
                const uint4* fp = sc->fx + j * 4 * 256 + tid;
                uint4 f0, f1, f2, f3;
                spin_until([&] {
                    f0 = peek(fp); f1 = peek(fp + 256); f2 = peek(fp + 512); f3 = peek(fp + 768);
                    return fresh(f0, tag) && fresh(f1, tag) && fresh(f2, tag) && fresh(f3, tag);
                });
#define GATE(e) silu(rbf((untag(f0.e) + untag(f1.e)) + (untag(f2.e) + untag(f3.e))))
                gw = pack2(GATE(x), GATE(z));
                gate1 = pack2(GATE(y), GATE(w));
#undef GATE
                __syncwarp();
            }
            const uint64_t ap = (uint64_t)(sc->acc + b * 512 + tid), op = (uint64_t)(out + b * DM + 2 * tid);
            const uint64_t sp = (uint64_t)(sc->sx + (b * NH + h) * 256 + tid);
            sts128(sb + SM_FIN + tid * 16, make_uint4((uint32_t)ap, ap >> 32, (uint32_t)sp, sp >> 32));
            sts128(sb + SM_FIN + 4096 + tid * 16, make_uint4((uint32_t)op, op >> 32, gw, xw));
        });
        float acc[4][4] = {};
        uint4 fin0, fin1;
#pragma unroll
        for (int kk = 0; kk < 4; kk++) {
            const uint4 b = lds128(sb + SM_O + (kk * 32 + 8 * t) * 2);
            if (kk == 3) { fin0 = lds128(sb + SM_FIN + tid * 16); fin1 = lds128(sb + SM_FIN + 4096 + tid * 16); }
#pragma unroll
            for (int i = 0; i < 4; i++) mma(acc[i], wof[2 * kk][i][0], wof[2 * kk][i][1], wof[2 * kk][i][2], wof[2 * kk][i][3], b.x, b.y);
#pragma unroll
            for (int i = 0; i < 4; i++) mma(acc[i], wof[2 * kk + 1][i][0], wof[2 * kk + 1][i][1], wof[2 * kk + 1][i][2], wof[2 * kk + 1][i][3], b.z, b.w);
        }
        const uint64_t ap = (uint64_t)fin0.y << 32 | fin0.x, sp = (uint64_t)fin0.w << 32 | fin0.z, op = (uint64_t)fin1.y << 32 | fin1.x;
        const float va = (t & 2) ? ((t & 1) ? acc[3][0] : acc[2][0]) : ((t & 1) ? acc[1][0] : acc[0][0]);
        const float vb = (t & 2) ? ((t & 1) ? acc[3][2] : acc[2][2]) : ((t & 1) ? acc[1][2] : acc[0][2]);
        const unsigned long long fa = to_fixed(va), fb = to_fixed(vb);
        uint32_t alo, ahi, blo, bhi;
        asm volatile("{ .reg .b64 ta, tb;\n"
                     "st.relaxed.gpu.global.v2.u32 [%5], {%6,%7};\n"
                     "atom.relaxed.gpu.global.add.u64 ta, [%4], %8;\n"
                     "atom.relaxed.gpu.global.add.u64 tb, [%4+2048], %9;\n"
                     "add.u64 ta, ta, %8;\n"
                     "add.u64 tb, tb, %9;\n"
                     "mov.b64 {%0,%1}, ta;\n"
                     "mov.b64 {%2,%3}, tb; }"
                     : "=r"(alo), "=r"(ahi), "=r"(blo), "=r"(bhi)
                     : "l"(ap), "l"(sp), "r"((__float_as_uint(va) & ~3u) | tag), "r"((__float_as_uint(vb) & ~3u) | tag),
                       "l"(fa), "l"(fb) : "memory");
        const float s0 = from_fixed(alo, ahi), s1 = from_fixed(blo, bhi);
        uint32_t ow = combine(s0, s1, fin1.z, fin1.w);
        const bool last_a = alo & NH, last_b = blo & NH;
        if (last_a) st_out(op, ow);
        if (last_b) st_out(op + 2, ow >> 16);
        if (last_a) asm volatile("st.global.u64 [%0], 0;" :: "l"(ap) : "memory");
        if (last_b) asm volatile("st.global.u64 [%0+2048], 0;" :: "l"(ap) : "memory");
        const bool redo_a = last_a & needs_fp32(alo, s0), redo_b = last_b & needs_fp32(blo, s1);
        if (redo_a | redo_b) {
            const float2 s = sum_fp32((const uint2*)sp - h * 256, tag);
            ow = combine(s.x, s.y, fin1.z, fin1.w);
            if (redo_a) st_out(op, ow);
            if (redo_b) st_out(op + 2, ow >> 16);
        }
        __syncwarp();
    }
}

__global__ void __launch_bounds__(NTHREADS, 1)
fused_decode_kernel(const bf16* __restrict__ x, const bf16* __restrict__ kc, const bf16* __restrict__ vc,
                    const bf16* __restrict__ wq, const bf16* __restrict__ wo, const bf16* __restrict__ wg,
                    const bf16* __restrict__ wu, const bf16* __restrict__ wd, bf16* __restrict__ out, Scratch* sc) {
    extern __shared__ __align__(128) unsigned char smem[];
    const uint32_t sb = (uint32_t)__cvta_generic_to_shared(smem);
    const int warp = threadIdx.x >> 5, lane = threadIdx.x & 31;
    const int h = blockIdx.x >> 2, j = blockIdx.x & 3;
    const char* k0 = cache_of(kc, h, j, 0);
    asm volatile("prefetch.global.L2 [%0];" :: "l"(k0 + TILE_BYTES + threadIdx.x * 32));
    if (threadIdx.x == 0) {
        const uint64_t pol = stream_policy();
#pragma unroll
        for (int s = 1; s <= DEPTH1; s++) {
            mbar_init(sb + SM_FULL + s * 8, 1);
            asm volatile("fence.mbarrier_init.release.cluster;" ::: "memory");
            mbar_expect_tx(sb + SM_FULL + s * 8, TILE_BYTES);
            bulk_load(sb + s * TILE_BYTES, k0 + (s - 1) * TILE_BYTES, TILE_BYTES, sb + SM_FULL + s * 8, pol);
        }
    }
    if (warp < 4) {
        asm volatile("setmaxnreg.dec.sync.aligned.u32 88;");
        if (warp == 0) {
            if (lane == 0) {
#pragma unroll
                for (int s = 0; s < STAGES; s++) {
                    if (s == 0 || s > DEPTH1) mbar_init(sb + SM_FULL + s * 8, 1);
                    mbar_init(sb + SM_EMPTY + s * 8, 8);
                }
#pragma unroll
                for (int w = 0; w < 8; w++) mbar_init(sb + SM_LAST + w * 8, 1);
                asm volatile("fence.mbarrier_init.release.cluster;" ::: "memory");
                mbar_arrive(sb + SM_FULL);
            }
            __syncwarp();
            asm volatile("bar.arrive 2, 320;" ::: "memory");
            if (lane == 0) producer(sb, h, j, kc, vc, wo, sc);
        } else if (warp == 1) {
            glu_warp(sb, h, j, wg, wu, wd, sc);
        }
    } else {
        consumer(sb, h, j, x, wq, out, sc);
    }
}

}

extern "C" void kernel_launch(void* const* d_in, const int* in_sizes, int n_in, void* d_out, int out_size) {
    static Scratch* scratch = nullptr;
    if (!scratch) {
        cudaFuncSetAttribute(fused_decode_kernel, cudaFuncAttributeMaxDynamicSharedMemorySize, SM_TOTAL);
        cudaGetSymbolAddress((void**)&scratch, g_scratch);
    }
    fused_decode_kernel<<<NCTA, NTHREADS, SM_TOTAL>>>(
        (const bf16*)d_in[0], (const bf16*)d_in[1], (const bf16*)d_in[2], (const bf16*)d_in[3], (const bf16*)d_in[4],
        (const bf16*)d_in[6], (const bf16*)d_in[7], (const bf16*)d_in[8], (bf16*)d_out, scratch);
}
```

```cpp
#include <cuda_runtime.h>
#include <cuda_bf16.h>
#include <stdint.h>

namespace {

typedef __nv_bfloat16 bf16;

constexpr int DM = 512, NH = 32, SK = 4096, DH = 128, FF = 1792;
constexpr int NCTA = 128, NTHREADS = 384;
constexpr int TILE_BYTES = 32768, STAGES = 6, TILES = SK * DH * 2 / TILE_BYTES;
constexpr int DEPTH1 = 2, DEPTH_SWITCH = 6, DEPTH2 = 3;
constexpr float PACE_BASE = 0.65f, PACE_GAIN = 3.0f, PACE_MAX = 1.5f;
constexpr int NPRE = 4;
constexpr int MID_AT = 24;

constexpr int XN_STRIDE = DM * 2 + 64;
constexpr int SM_P = STAGES * TILE_BYTES;
constexpr int SM_XN = SM_P + SK * 2;
constexpr int SM_RED = SM_XN + 8 * XN_STRIDE;
constexpr int SM_FIN = SM_RED + 8 * DH * 4;
constexpr int SM_Q = SM_FIN + 256 * 32;
constexpr int SM_O = SM_Q + 2 * DH * 2;
constexpr int SM_STAT = SM_O + DH * 2;
constexpr int SM_EPOCH = SM_STAT + 64;
constexpr int SM_FULL = SM_EPOCH + 16;
constexpr int SM_EMPTY = SM_FULL + STAGES * 8;
constexpr int SM_LAST = SM_EMPTY + STAGES * 8;
constexpr int SM_TOTAL = SM_LAST + 64;

struct __align__(256) Scratch {
    uint4 qx[NH * 4 * 4 * 64];
    uint4 hx[8 * FF / 4];
    uint4 fx[4 * 4 * 256];
    uint2 sx[8 * NH * 256];
    unsigned long long acc[8 * 2 * 256];
    unsigned epoch;
    unsigned pad[63];
    unsigned progress;
};
__device__ Scratch g_scratch;

__device__ __forceinline__ void mbar_init(uint32_t bar, uint32_t count) {
    asm volatile("mbarrier.init.shared::cta.b64 [%0], %1;" :: "r"(bar), "r"(count) : "memory");
}
__device__ __forceinline__ void mbar_expect_tx(uint32_t bar, uint32_t bytes) {
    asm volatile("mbarrier.arrive.expect_tx.shared::cta.b64 _, [%0], %1;" :: "r"(bar), "r"(bytes) : "memory");
}
__device__ __forceinline__ void mbar_arrive(uint32_t bar) {
    asm volatile("mbarrier.arrive.shared::cta.b64 _, [%0];" :: "r"(bar) : "memory");
}
template <int LIMIT = 1 << 16, typename F>
__device__ __forceinline__ void spin_until(F done) {
    int it = 0;
    while (!done() && ++it < LIMIT) {}
}
__device__ __forceinline__ void mbar_wait(uint32_t bar, uint32_t parity) {
    spin_until<1 << 14>([&] {
        uint32_t ok;
        asm volatile("{ .reg .pred p; mbarrier.try_wait.parity.shared::cta.b64 p, [%1], %2; selp.u32 %0, 1, 0, p; }"
                     : "=r"(ok) : "r"(bar), "r"(parity) : "memory");
        return ok != 0;
    });
}
__device__ __forceinline__ void bulk_load(uint32_t dst, const void* src, uint32_t bytes, uint32_t bar, uint64_t pol) {
    asm volatile("cp.async.bulk.shared::cluster.global.mbarrier::complete_tx::bytes.L2::cache_hint [%0], [%1], %2, [%3], %4;"
                 :: "r"(dst), "l"(src), "r"(bytes), "r"(bar), "l"(pol) : "memory");
}
__device__ __forceinline__ uint64_t stream_policy() {
    uint64_t pol;
    asm volatile("createpolicy.fractional.L2::evict_first.b64 %0, 1.0;" : "=l"(pol));
    return pol;
}
__device__ __forceinline__ int cons_tid() { return threadIdx.x - 128; }
__device__ __forceinline__ void cons_sync() { asm volatile("bar.sync 1, 256;" ::: "memory"); }

__device__ __forceinline__ uint4 lds128(uint32_t a) {
    uint4 v;
    asm volatile("ld.shared.v4.u32 {%0,%1,%2,%3}, [%4];" : "=r"(v.x), "=r"(v.y), "=r"(v.z), "=r"(v.w) : "r"(a) : "memory");
    return v;
}
__device__ __forceinline__ uint32_t lds32(uint32_t a) {
    uint32_t v;
    asm volatile("ld.shared.u32 %0, [%1];" : "=r"(v) : "r"(a) : "memory");
    return v;
}
__device__ __forceinline__ float2 lds64f(uint32_t a) {
    float2 v;
    asm volatile("ld.shared.v2.f32 {%0,%1}, [%2];" : "=f"(v.x), "=f"(v.y) : "r"(a) : "memory");
    return v;
}
__device__ __forceinline__ void sts128(uint32_t a, uint4 v) {
    asm volatile("st.shared.v4.u32 [%0], {%1,%2,%3,%4};" :: "r"(a), "r"(v.x), "r"(v.y), "r"(v.z), "r"(v.w) : "memory");
}
__device__ __forceinline__ void sts64f(uint32_t a, float x, float y) {
    asm volatile("st.shared.v2.f32 [%0], {%1,%2};" :: "r"(a), "f"(x), "f"(y) : "memory");
}
__device__ __forceinline__ void sts32(uint32_t a, uint32_t v) {
    asm volatile("st.shared.u32 [%0], %1;" :: "r"(a), "r"(v) : "memory");
}
__device__ __forceinline__ void sts16(uint32_t a, uint32_t v) {
    asm volatile("st.shared.u16 [%0], %1;" :: "r"(a), "h"((uint16_t)v) : "memory");
}
__device__ __forceinline__ uint4 ldsm4(uint32_t a) {
    uint4 v;
    asm volatile("ldmatrix.sync.aligned.m8n8.x4.shared.b16 {%0,%1,%2,%3}, [%4];"
                 : "=r"(v.x), "=r"(v.y), "=r"(v.z), "=r"(v.w) : "r"(a) : "memory");
    return v;
}
__device__ __forceinline__ uint4 ldsm4t(uint32_t a) {
    uint4 v;
    asm volatile("ldmatrix.sync.aligned.m8n8.x4.trans.shared.b16 {%0,%1,%2,%3}, [%4];"
                 : "=r"(v.x), "=r"(v.y), "=r"(v.z), "=r"(v.w) : "r"(a) : "memory");
    return v;
}
__device__ __forceinline__ void cp_async16(uint32_t dst, const void* src) {
    asm volatile("cp.async.cg.shared.global [%0], [%1], 16;" :: "r"(dst), "l"(src) : "memory");
}
__device__ __forceinline__ uint4 ldg128(const void* p) {
    uint4 v;
    asm volatile("ld.global.nc.L1::no_allocate.v4.u32 {%0,%1,%2,%3}, [%4];" : "=r"(v.x), "=r"(v.y), "=r"(v.z), "=r"(v.w) : "l"(p));
    return v;
}
__device__ __forceinline__ uint32_t ldg32(const void* p) {
    uint32_t v;
    asm volatile("ld.global.nc.L1::no_allocate.L2::128B.u32 %0, [%1];" : "=r"(v) : "l"(p));
    return v;
}
__device__ __forceinline__ void mma(float (&c)[4], uint32_t a0, uint32_t a1, uint32_t a2, uint32_t a3, uint32_t b0, uint32_t b1) {
    asm volatile("mma.sync.aligned.m16n8k16.row.col.f32.bf16.bf16.f32 {%0,%1,%2,%3}, {%4,%5,%6,%7}, {%8,%9}, {%0,%1,%2,%3};"
                 : "+f"(c[0]), "+f"(c[1]), "+f"(c[2]), "+f"(c[3])
                 : "r"(a0), "r"(a1), "r"(a2), "r"(a3), "r"(b0), "r"(b1));
}
__device__ __forceinline__ uint32_t lo2(uint32_t a, uint32_t b) { return __byte_perm(a, b, 0x5410); }
__device__ __forceinline__ uint32_t hi2(uint32_t a, uint32_t b) { return __byte_perm(a, b, 0x7632); }
__device__ __forceinline__ float bf_lo(uint32_t w) { return __uint_as_float(w << 16); }
__device__ __forceinline__ float bf_hi(uint32_t w) { return __uint_as_float(w & 0xffff0000u); }
__device__ __forceinline__ float rbf(float v) { return __bfloat162float(__float2bfloat16_rn(v)); }
__device__ __forceinline__ uint32_t pack2(float lo, float hi) {
    __nv_bfloat162 v = __floats2bfloat162_rn(lo, hi);
    return *reinterpret_cast<uint32_t*>(&v);
}

__device__ __forceinline__ void publish(uint4* p, float a, float b, float c, float d, uint32_t tag) {
    asm volatile("st.relaxed.gpu.global.v4.u32 [%0], {%1,%2,%3,%4};" :: "l"(p),
                 "r"((__float_as_uint(a) & ~3u) | tag), "r"((__float_as_uint(b) & ~3u) | tag),
                 "r"((__float_as_uint(c) & ~3u) | tag), "r"((__float_as_uint(d) & ~3u) | tag) : "memory");
}
__device__ __forceinline__ uint4 peek(const uint4* p) {
    uint4 v;
    asm volatile("ld.relaxed.gpu.global.v4.u32 {%0,%1,%2,%3}, [%4];" : "=r"(v.x), "=r"(v.y), "=r"(v.z), "=r"(v.w) : "l"(p) : "memory");
    return v;
}
__device__ __forceinline__ bool fresh(uint4 v, uint32_t tag) {
    return (((v.x ^ tag) | (v.y ^ tag) | (v.z ^ tag) | (v.w ^ tag)) & 3u) == 0;
}
__device__ __forceinline__ float untag(uint32_t w) { return __uint_as_float(w & ~3u); }
__device__ __forceinline__ uint4 wait_fresh(const uint4* p, uint32_t tag) {
    uint4 v;
    spin_until([&] { v = peek(p); return fresh(v, tag); });
    return v;
}
__device__ __forceinline__ float reduce_scatter4(float a, float b, float c, float d, int lane) {
    const bool up = lane & 16;
    float k0 = (up ? c : a) + __shfl_xor_sync(~0u, up ? a : c, 16);
    float k1 = (up ? d : b) + __shfl_xor_sync(~0u, up ? b : d, 16);
    const bool odd = lane & 8;
    return (odd ? k1 : k0) + __shfl_xor_sync(~0u, odd ? k0 : k1, 8);
}

__device__ __forceinline__ void layernorm_row(uint4 r0, uint4 r1, uint32_t dst, int lane) {
    const uint32_t w[8] = {r0.x, r0.y, r0.z, r0.w, r1.x, r1.y, r1.z, r1.w};
    float v[16], s = 0.f;
#pragma unroll
    for (int i = 0; i < 8; i++) { v[2 * i] = bf_lo(w[i]); v[2 * i + 1] = bf_hi(w[i]); s += v[2 * i] + v[2 * i + 1]; }
#pragma unroll
    for (int o = 16; o; o >>= 1) s += __shfl_xor_sync(~0u, s, o);
    const float mean = s * (1.f / DM);
    float q = 0.f;
#pragma unroll
    for (int i = 0; i < 16; i++) q += (v[i] - mean) * (v[i] - mean);
#pragma unroll
    for (int o = 16; o; o >>= 1) q += __shfl_xor_sync(~0u, q, o);
    const float mb = rbf(mean);
    const float den = rbf(__fsqrt_rn(rbf(rbf(q * (1.f / DM)) + 1e-5f)));
    const float inv = __frcp_rn(den);
    uint32_t o[8];
#pragma unroll
    for (int i = 0; i < 8; i++) {
        const uint32_t d = pack2(v[2 * i] - mb, v[2 * i + 1] - mb);
        o[i] = pack2(bf_lo(d) * inv, bf_hi(d) * inv);
    }
    sts128(dst + lane * 16, make_uint4(o[0], o[1], o[2], o[3]));
    sts128(dst + 512 + lane * 16, make_uint4(o[4], o[5], o[6], o[7]));
}

__device__ __forceinline__ void gemv_step(float (&c)[4], const uint32_t (&r)[8], uint4 b) {
    mma(c, lo2(r[0], r[1]), hi2(r[0], r[1]), lo2(r[2], r[3]), hi2(r[2], r[3]), b.x, b.y);
    mma(c, lo2(r[4], r[5]), hi2(r[4], r[5]), lo2(r[6], r[7]), hi2(r[6], r[7]), b.z, b.w);
}
__device__ __forceinline__ void load_rows(uint32_t (&r)[8], const bf16* p, int stride) {
#pragma unroll
    for (int i = 0; i < 8; i++) r[i] = ldg32(p + i * stride);
}

__device__ __forceinline__ int batch_of(int j, int i) { return j + 4 * i; }
__device__ __forceinline__ const char* cache_of(const bf16* cache, int h, int j, int i) {
    return (const char*)cache + ((size_t)(batch_of(j, i) * NH + h) << 20);
}

struct Ring {
    uint32_t stage, phase;
    __device__ __forceinline__ void next() { if (++stage == STAGES) { stage = 0; phase ^= 1; } }
};
__device__ __forceinline__ void release(uint32_t sb, Ring& ring, int lane, uint32_t dep) {
    __syncwarp();
    if (lane == 0) mbar_arrive(sb + SM_EMPTY + ring.stage * 8 + (dep & blockIdx.y));
    ring.next();
}

constexpr int WO_STEP = (TILES - NPRE) / 4;
__device__ __forceinline__ int wo_first(int h) { return NPRE + h % WO_STEP; }

__device__ __forceinline__ void producer(uint32_t sb, int h, int j, const bf16* kc, const bf16* vc, const bf16* wo,
                                         Scratch* sc) {
    const uint64_t pol = stream_policy();
    Ring ring = {1 + DEPTH1, 1}, landed = {1, 0};
    int inflight = DEPTH1, counted = 0, wo_at = wo_first(h);
    const uint32_t t_start = clock();
    uint32_t t_prev = t_start;
    unsigned total = 0;
    auto acquire = [&](int depth) {
        for (; inflight >= depth; inflight--) {
            mbar_wait(sb + SM_FULL + landed.stage * 8, landed.phase);
            landed.next();
        }
        mbar_wait(sb + SM_EMPTY + ring.stage * 8, ring.phase);
    };
    auto pace = [&] {
        const float lead = (float)(counted * NCTA - NCTA / 2 - (int)total);
        const float per = __fdividef((float)(t_prev - t_start), (float)(total + DEPTH1 * NCTA));
        const float periods = fminf(fmaxf(PACE_BASE * NCTA + PACE_GAIN * lead, 0.f), PACE_MAX * NCTA);
        const uint32_t gap = (uint32_t)fminf(per * periods, 8192.f);
        acquire(counted < DEPTH_SWITCH ? DEPTH1 : DEPTH2);
        while ((uint32_t)clock() - t_prev < gap) {}
    };
    auto issue = [&](const char* src) {
        mbar_expect_tx(sb + SM_FULL + ring.stage * 8, TILE_BYTES);
        bulk_load(sb + ring.stage * TILE_BYTES, src, TILE_BYTES, sb + SM_FULL + ring.stage * 8, pol);
        ring.next();
        inflight++;
    };
#pragma unroll 1
    for (int seg = 0; seg < 4; seg++) {
        const char* src = cache_of((seg & 1) ? vc : kc, h, j, seg >> 1);
#pragma unroll 1
        for (int it = seg ? 0 : DEPTH1; it < TILES - (seg == 3); it++) {
            pace();
            issue(src + it * TILE_BYTES);
            t_prev = clock();
            total = atomicAdd(&sc->progress, 1);
            counted++;
            if (seg == 0 && it == wo_at) {
                acquire(STAGES);
                issue((const char*)wo + (size_t)(h * 4 + (it - NPRE) / WO_STEP) * TILE_BYTES);
                wo_at += WO_STEP;
            }
        }
    }
    pace();
    const char* src = cache_of(vc, h, j, 1) + (TILES - 1) * TILE_BYTES;
#pragma unroll 1
    for (int w = 0; w < 8; w++) {
        mbar_expect_tx(sb + SM_LAST + w * 8, TILE_BYTES / 8);
        bulk_load(sb + ring.stage * TILE_BYTES + w * (TILE_BYTES / 8), src + w * (TILE_BYTES / 8), TILE_BYTES / 8,
                  sb + SM_LAST + w * 8, pol);
    }
    if (total == NCTA * (4 * TILES - 1 - DEPTH1) - 1) {
        sc->progress = 0;
        sc->epoch = lds32(sb + SM_EPOCH) + 1;
    }
}

__device__ __forceinline__ void glu_warp(uint32_t sb, int h, int j, const bf16* wg, const bf16* wu, const bf16* wd, Scratch* sc) {
    const int lane = threadIdx.x & 31, g = lane >> 2, t = lane & 3;
    asm volatile("bar.sync 2, 320;" ::: "memory");
    const uint32_t tag = (lds32(sb + SM_EPOCH) + 1) & 3;
    sc->acc[batch_of(j, lane >> 4) * 512 + (lane & 8) * 32 + h * 8 + (lane & 7)] = 0;
    if ((blockIdx.x & 7) != 7) {
        const int f0 = ((blockIdx.x >> 3) * 7 + (blockIdx.x & 7)) * 16 + 2 * g;
        float cg[4] = {}, cu[4] = {};
#pragma unroll 1
        for (int k = 8 * t; k < DM; k += 64) {
            uint32_t g0[8], g1[8], u0[8], u1[8];
            load_rows(g0, wg + k * FF + f0, FF);
            load_rows(u0, wu + k * FF + f0, FF);
            load_rows(g1, wg + (k + 32) * FF + f0, FF);
            load_rows(u1, wu + (k + 32) * FF + f0, FF);
            const uint4 b0 = lds128(sb + SM_XN + g * XN_STRIDE + k * 2), b1 = lds128(sb + SM_XN + g * XN_STRIDE + k * 2 + 64);
            gemv_step(cg, g0, b0);
            gemv_step(cu, u0, b0);
            gemv_step(cg, g1, b1);
            gemv_step(cu, u1, b1);
        }
        uint32_t hw[4];
#pragma unroll
        for (int e = 0; e < 4; e++) hw[e] = __float_as_uint(rbf(rbf(cg[e]) * rbf(cu[e]))) | tag;
        uint32_t* dst = (uint32_t*)sc->hx + 2 * t * FF + f0;
        asm volatile("st.relaxed.gpu.global.v2.u32 [%0], {%1,%2};" :: "l"(dst), "r"(hw[0]), "r"(hw[2]) : "memory");
        asm volatile("st.relaxed.gpu.global.v2.u32 [%0], {%1,%2};" :: "l"(dst + FF), "r"(hw[1]), "r"(hw[3]) : "memory");
    }
    {
        float c[4] = {};
#pragma unroll 1
        for (int k = j * (FF / 4) + 8 * t; k < (j + 1) * (FF / 4); k += 64) {
            uint32_t r0[8], r1[8];
            load_rows(r0, wd + k * DM + h * 16 + 2 * g, DM);
            load_rows(r1, wd + (k + 32) * DM + h * 16 + 2 * g, DM);
            const uint4* hp = sc->hx + (g * FF + k) / 4;
            uint4 a0, a1, a2, a3;
            spin_until([&] {
                a0 = peek(hp); a1 = peek(hp + 1); a2 = peek(hp + 8); a3 = peek(hp + 9);
                return fresh(a0, tag) && fresh(a1, tag) && fresh(a2, tag) && fresh(a3, tag);
            });
            __syncwarp();
            gemv_step(c, r0, make_uint4(hi2(a0.x, a0.y), hi2(a0.z, a0.w), hi2(a1.x, a1.y), hi2(a1.z, a1.w)));
            gemv_step(c, r1, make_uint4(hi2(a2.x, a2.y), hi2(a2.z, a2.w), hi2(a3.x, a3.y), hi2(a3.z, a3.w)));
        }
        asm volatile("fence.acq_rel.gpu;" ::: "memory");
        publish(sc->fx + (t * 4 + j) * 256 + h * 8 + g, c[0], c[1], c[2], c[3], tag);
    }
}

__device__ __forceinline__ void keep_wo_tile(uint32_t sb, Ring& ring, uint32_t (&lo)[4][4], uint32_t (&hi)[4][4]) {
    const int warp = cons_tid() >> 5, lane = threadIdx.x & 31, g = lane >> 2, t = lane & 3;
    mbar_wait(sb + SM_FULL + ring.stage * 8, ring.phase);
    const uint32_t base = sb + ring.stage * TILE_BYTES + t * 8192 + warp * 128 + g * 16;
    uint4 r[8];
#pragma unroll
    for (int i = 0; i < 8; i++) r[i] = lds128(base + i * 1024);
#define WO_TILE(i, f) \
    lo[i][0] = lo2(r[0].f, r[1].f); lo[i][1] = hi2(r[0].f, r[1].f); lo[i][2] = lo2(r[2].f, r[3].f); lo[i][3] = hi2(r[2].f, r[3].f); \
    hi[i][0] = lo2(r[4].f, r[5].f); hi[i][1] = hi2(r[4].f, r[5].f); hi[i][2] = lo2(r[6].f, r[7].f); hi[i][3] = hi2(r[6].f, r[7].f);
    WO_TILE(0, x) WO_TILE(1, y) WO_TILE(2, z) WO_TILE(3, w)
#undef WO_TILE
    release(sb, ring, lane, lo[0][0] | lo[0][2] | hi[0][0] | hi[0][2]);
}

__device__ __forceinline__ void load_q(uint32_t sb, int pr, uint4 (&q)[4]) {
    const int lane = threadIdx.x & 31, g = lane >> 2, t = lane & 3;
#pragma unroll
    for (int j = 0; j < 4; j++) q[j] = lds128(sb + SM_Q + pr * (DH * 2) + (4 * (j ^ (g & 1)) + t) * 16);
}
__device__ __forceinline__ void load_k(uint32_t sb, const Ring& ring, uint4 (&k)[8]) {
    const int warp = cons_tid() >> 5, lane = threadIdx.x & 31, g = lane >> 2, t = lane & 3;
    mbar_wait(sb + SM_FULL + ring.stage * 8, ring.phase);
    const uint32_t base = sb + ring.stage * TILE_BYTES + (warp * 16 + g) * 256 + t * 16, swap = (g & 1) * 64;
#pragma unroll
    for (int j = 0; j < 4; j++) {
        k[2 * j] = lds128(base + ((j * 64) ^ swap));
        k[2 * j + 1] = lds128(base + 2048 + ((j * 64) ^ swap));
    }
}
__device__ __forceinline__ uint32_t score_tile(uint32_t sb, int it, const uint4 (&k)[8], const uint4 (&q)[4]) {
    const int warp = cons_tid() >> 5, lane = threadIdx.x & 31, g = lane >> 2, t = lane & 3;
    float c0[4] = {}, c1[4] = {};
#pragma unroll
    for (int j = 0; j < 4; j++) {
        mma(c0, k[2 * j].x, k[2 * j + 1].x, k[2 * j].y, k[2 * j + 1].y, q[j].x, q[j].y);
        mma(c1, k[2 * j].z, k[2 * j + 1].z, k[2 * j].w, k[2 * j + 1].w, q[j].z, q[j].w);
    }
    const float lo = (g & 1) ? c0[1] + c1[1] : c0[0] + c1[0];
    const float hi = (g & 1) ? c0[3] + c1[3] : c0[2] + c1[2];
    const float s = rbf((t & 1) ? hi : lo) * 0.08838834764831845f;
    if (t < 2) sts16(sb + SM_P + warp * 1024 + it * 32 + (g + 8 * t) * 2, __bfloat16_as_ushort(__float2bfloat16_rn(s)));
    return __float_as_uint(lo);
}
__device__ __forceinline__ void phase_qk(uint32_t sb, Ring& ring, int pr, int wo_at, uint32_t (&wof)[8][4][4]) {
    uint4 q[4];
    load_q(sb, pr, q);
#pragma unroll 1
    for (int it = pr ? 0 : NPRE; it < TILES; it++) {
        uint4 k[8];
        load_k(sb, ring, k);
        release(sb, ring, threadIdx.x & 31, score_tile(sb, it, k, q));
        if (it == wo_at) {
            wo_at += WO_STEP;
            switch ((it - NPRE) / WO_STEP) {
                case 0: keep_wo_tile(sb, ring, wof[0], wof[1]); break;
                case 1: keep_wo_tile(sb, ring, wof[2], wof[3]); break;
                case 2: keep_wo_tile(sb, ring, wof[4], wof[5]); break;
                default: keep_wo_tile(sb, ring, wof[6], wof[7]); break;
            }
        }
    }
}

__device__ __forceinline__ void phase_softmax(uint32_t sb) {
    const int warp = cons_tid() >> 5, lane = threadIdx.x & 31;
    const uint32_t a = sb + SM_P + warp * 1024 + lane * 16;
    __syncwarp();
    const uint4 r0 = lds128(a), r1 = lds128(a + 512);
    const uint32_t w[8] = {r0.x, r0.y, r0.z, r0.w, r1.x, r1.y, r1.z, r1.w};
    float v[16], m = -INFINITY;
#pragma unroll
    for (int i = 0; i < 8; i++) { v[2 * i] = bf_lo(w[i]); v[2 * i + 1] = bf_hi(w[i]); m = fmaxf(m, fmaxf(v[2 * i], v[2 * i + 1])); }
#pragma unroll
    for (int o = 16; o; o >>= 1) m = fmaxf(m, __shfl_xor_sync(~0u, m, o));
    if (lane == 0) sts32(sb + SM_STAT + warp * 4, __float_as_uint(m));
    cons_sync();
    {
        const uint4 s0 = lds128(sb + SM_STAT), s1 = lds128(sb + SM_STAT + 16);
        m = fmaxf(fmaxf(fmaxf(__uint_as_float(s0.x), __uint_as_float(s0.y)), fmaxf(__uint_as_float(s0.z), __uint_as_float(s0.w))),
                  fmaxf(fmaxf(__uint_as_float(s1.x), __uint_as_float(s1.y)), fmaxf(__uint_as_float(s1.z), __uint_as_float(s1.w))));
    }
    float l = 0.f;
#pragma unroll
    for (int i = 0; i < 16; i++) { v[i] = expf(v[i] - m); l += v[i]; }
#pragma unroll
    for (int o = 16; o; o >>= 1) l += __shfl_xor_sync(~0u, l, o);
    if (lane == 0) sts32(sb + SM_STAT + 32 + warp * 4, __float_as_uint(l));
    cons_sync();
    {
        const uint4 s0 = lds128(sb + SM_STAT + 32), s1 = lds128(sb + SM_STAT + 48);
        l = ((__uint_as_float(s0.x) + __uint_as_float(s0.y)) + (__uint_as_float(s0.z) + __uint_as_float(s0.w))) +
            ((__uint_as_float(s1.x) + __uint_as_float(s1.y)) + (__uint_as_float(s1.z) + __uint_as_float(s1.w)));
    }
    const float inv = 1.f / l;
    uint32_t o[8];
#pragma unroll
    for (int i = 0; i < 8; i++) o[i] = pack2(v[2 * i] * inv, v[2 * i + 1] * inv);
    sts128(a, make_uint4(o[0], o[1], o[2], o[3]));
    sts128(a + 512, make_uint4(o[4], o[5], o[6], o[7]));
    __syncwarp();
}

__device__ __forceinline__ uint32_t prmt_now(uint32_t a, uint32_t sel) {
    uint32_t d;
    asm volatile("prmt.b32 %0, %1, 0, %2;" : "=r"(d) : "r"(a), "r"(sel) : "memory");
    return d;
}
template <typename F>
__device__ __forceinline__ void phase_pv(uint32_t sb, Ring& ring, int pr, F midway) {
    const int tid = cons_tid(), warp = tid >> 5, lane = tid & 31, g = lane >> 2, t = lane & 3;
    const uint32_t sel0 = g == 2 * t ? 0x4410 : g == 2 * t + 1 ? 0x1044 : 0x4444;
    const uint32_t sel1 = g == 2 * t ? 0x4432 : g == 2 * t + 1 ? 0x3244 : 0x4444;
    uint32_t psrc = sb + SM_P + warp * 1024;
    float c0[4] = {}, c1[4] = {};
    auto tile = [&](uint32_t bar, uint32_t parity) {
        const uint4 pa = lds128(psrc), pb = lds128(psrc + 16);
        psrc += 32;
        const uint32_t p[8] = {pa.x, pa.y, pa.z, pa.w, pb.x, pb.y, pb.z, pb.w};
        uint32_t b0[8], b1[8];
#pragma unroll
        for (int j = 0; j < 8; j++) { b0[j] = prmt_now(p[j], sel0); b1[j] = prmt_now(p[j], sel1); }
        const uint32_t base = sb + ring.stage * TILE_BYTES + warp * 4096 + lane * 16;
        mbar_wait(bar, parity);
        uint4 v[8];
#pragma unroll
        for (int j = 0; j < 8; j++) v[j] = ldsm4(base + j * 512);
#pragma unroll
        for (int j = 0; j < 8; j += 2) {
            mma(c0, v[j].x, v[j].y, v[j].z, v[j].w, b0[j], b1[j]);
            mma(c1, v[j + 1].x, v[j + 1].y, v[j + 1].z, v[j + 1].w, b0[j + 1], b1[j + 1]);
        }
    };
#pragma unroll 1
    for (int it = 0; it < TILES - 1; it++) {
        tile(sb + SM_FULL + ring.stage * 8, ring.phase);
        release(sb, ring, lane, __float_as_uint(c0[0]) | __float_as_uint(c1[0]));
        if (it == MID_AT) midway();
    }
    tile(pr ? sb + SM_LAST + warp * 8 : sb + SM_FULL + ring.stage * 8, pr ? 0 : ring.phase);
    sts64f(sb + SM_RED + warp * 512 + lane * 8, c0[0] + c1[0], c0[1] + c1[1]);
    sts64f(sb + SM_RED + warp * 512 + 256 + lane * 8, c0[2] + c1[2], c0[3] + c1[3]);
    cons_sync();
    if (tid == 64) asm volatile("mbarrier.arrive.shared::cta.b64 _, [%0], 8;" :: "r"(sb + SM_EMPTY + ring.stage * 8) : "memory");
    ring.next();
    if (tid < 64) {
        float2 r[8];
#pragma unroll
        for (int w = 0; w < 8; w++) r[w] = lds64f(sb + SM_RED + w * 512 + tid * 8);
        sts32(sb + SM_O + tid * 4,
              pack2(((r[0].x + r[1].x) + (r[2].x + r[3].x)) + ((r[4].x + r[5].x) + (r[6].x + r[7].x)),
                    ((r[0].y + r[1].y) + (r[2].y + r[3].y)) + ((r[4].y + r[5].y) + (r[6].y + r[7].y))));
    }
    cons_sync();
}

__device__ __forceinline__ unsigned long long to_fixed(float v) {
    const bool ok = fabsf(v) < 256.f;
    return ((unsigned long long)__float2ll_rn(ok ? v * 0x1p38f : 0.f) << 12) | (ok ? 1 : 65);
}
__device__ __forceinline__ float from_fixed(uint32_t lo, uint32_t hi) {
    return fmaf(__uint2float_rn(lo & ~0xfffu), 0x1p-50f, __int2float_rn((int)hi) * 0x1p-18f);
}
__device__ __forceinline__ bool needs_fp32(uint32_t lo, float s) { return ((lo & 0xfc0) != 0) | (fabsf(s) < 0x1p-20f); }
__device__ __forceinline__ uint32_t combine(float s0, float s1, uint32_t gw, uint32_t xw) {
    const uint32_t sw = pack2(s0, s1);
    const uint32_t mw = pack2(bf_lo(sw) * bf_lo(gw), bf_hi(sw) * bf_hi(gw));
    return pack2(bf_lo(xw) + bf_lo(mw), bf_hi(xw) + bf_hi(mw));
}
__device__ __noinline__ float2 sum_fp32(const uint2* parts, uint32_t tag) {
    float2 s = make_float2(0.f, 0.f);
#pragma unroll 1
    for (int i = 0; i < NH; i += 16) {
        uint2 w[16];
        spin_until([&] {
            uint32_t stale = 0;
#pragma unroll
            for (int k = 0; k < 16; k++)
                asm volatile("ld.relaxed.gpu.global.v2.u32 {%0,%1}, [%2];" : "=r"(w[k].x), "=r"(w[k].y) : "l"(parts + (i + k) * 256) : "memory");
#pragma unroll
            for (int k = 0; k < 16; k++) stale |= (w[k].x ^ tag) | (w[k].y ^ tag);
            return (stale & 3) == 0;
        });
#pragma unroll
        for (int k = 0; k < 16; k++) { s.x += untag(w[k].x); s.y += untag(w[k].y); }
    }
    return s;
}
__device__ __forceinline__ void st_out(uint64_t p, uint32_t v) {
    asm volatile("st.global.u16 [%0], %1;" :: "l"(p), "h"((uint16_t)v) : "memory");
}
__device__ __forceinline__ float silu(float d) { return d / (1.f + expf(-d)); }

__device__ __forceinline__ void consumer(uint32_t sb, int h, int j, const bf16* x, const bf16* wq, bf16* out, Scratch* sc) {
    const int tid = cons_tid(), warp = tid >> 5, lane = tid & 31, g = lane >> 2, t = lane & 3;
    uint32_t tag;
    Ring ring = {0, 0};
    {
        const int r = tid >> 4;
        const bf16* wp = wq + (unsigned)((128 * j + r) * (NH * DH) + h * DH + (tid & 15) * 8);
        const uint32_t dst = sb + r * 256 + (((tid & 15) ^ (r & 1) ^ ((r >> 2) & 2)) << 4);
#pragma unroll
        for (int i = 0; i < 8; i++) cp_async16((dst ^ ((i & 1) << 6)) + i * 4096, wp + i * 16 * (NH * DH));
        const bf16* xp = x + batch_of(warp >> 1, warp & 1) * DM + lane * 8;
        const uint4 x0 = ldg128(xp), x1 = ldg128(xp + 256);
        unsigned epoch;
        if (tid == 0) epoch = *(volatile unsigned*)&sc->epoch;
        asm volatile("setmaxnreg.inc.sync.aligned.u32 208;");
        layernorm_row(x0, x1, sb + SM_XN + warp * XN_STRIDE, lane);
        if (tid == 0) sts32(sb + SM_EPOCH, epoch);
        asm volatile("cp.async.wait_all;" ::: "memory");
        asm volatile("fence.proxy.async.shared::cta;" ::: "memory");
        asm volatile("bar.sync 2, 320;" ::: "memory");
        tag = (lds32(sb + SM_EPOCH) + 1) & 3;
        const uint32_t a = sb + (4 * (lane & 6) + (lane & 1) + 2 * (lane >> 4)) * 256 + (((2 * warp + ((lane >> 3) & 1)) ^ (lane & 7)) << 4);
        float c0[4] = {}, c1[4] = {};
#pragma unroll
        for (int kk = 0; kk < 4; kk++) {
            const uint4 b = lds128(sb + SM_XN + g * XN_STRIDE + (128 * j + kk * 32 + 8 * t) * 2);
            const uint4 a0 = ldsm4t(a + kk * 8192), a1 = ldsm4t(a + kk * 8192 + 1024);
            mma(c0, a0.x, a0.y, a0.z, a0.w, b.x, b.y);
            mma(c1, a1.x, a1.y, a1.z, a1.w, b.z, b.w);
        }
        publish(sc->qx + ((h * 4 + t) * 4 + j) * 64 + warp * 8 + g, c0[0] + c1[0], c0[1] + c1[1], c0[2] + c1[2], c0[3] + c1[3], tag);
        release(sb, ring, lane, __float_as_uint(c0[0]) | __float_as_uint(c1[0]));
        uint4 k[NPRE][8];
#pragma unroll
        for (int n = 0; n < NPRE; n++) {
            load_k(sb, ring, k[n]);
            release(sb, ring, lane, k[n][0].x | k[n][1].x | k[n][2].x | k[n][3].x | k[n][4].x | k[n][5].x | k[n][6].x | k[n][7].x);
        }
        const int hg = lane >> 3, cp = lane & 7;
        const uint4 f = wait_fresh(sc->qx + ((h * 4 + j) * 4 + hg) * 64 + warp * 8 + cp, tag);
        __syncwarp();
        const float qv = reduce_scatter4(untag(f.x), untag(f.y), untag(f.z), untag(f.w), lane);
        sts16(sb + SM_Q + (hg & 1) * (DH * 2) + (warp * 16 + cp + 8 * (hg >> 1)) * 2, __bfloat16_as_ushort(__float2bfloat16_rn(qv)));
        cons_sync();
        uint4 q[4];
        load_q(sb, 0, q);
#pragma unroll
        for (int n = 0; n < NPRE; n++) score_tile(sb, n, k[n], q);
    }

    uint32_t wof[8][4][4], gate1;
#pragma unroll
    for (int i = 0; i < 128; i++) asm volatile("" : "=r"(wof[i >> 4][(i >> 2) & 3][i & 3]));
    asm volatile("" : "=r"(gate1));
#pragma unroll 1
    for (int pr = 0; pr < 2; pr++) {
        phase_qk(sb, ring, pr, pr ? -1 : wo_first(h), wof);
        phase_softmax(sb);
        phase_pv(sb, ring, pr, [&] {
            const int b = batch_of(j, pr);
            const uint32_t xw = ((const uint32_t*)x)[b * 256 + tid];
            uint32_t gw = gate1;
            if (pr == 0) {
                const uint4* fp = sc->fx + j * 4 * 256 + tid;
                uint4 f0, f1, f2, f3;
                spin_until([&] {
                    f0 = peek(fp); f1 = peek(fp + 256); f2 = peek(fp + 512); f3 = peek(fp + 768);
                    return fresh(f0, tag) && fresh(f1, tag) && fresh(f2, tag) && fresh(f3, tag);
                });
                asm volatile("fence.acq_rel.gpu;" ::: "memory");
#define GATE(e) silu(rbf((untag(f0.e) + untag(f1.e)) + (untag(f2.e) + untag(f3.e))))
                gw = pack2(GATE(x), GATE(z));
                gate1 = pack2(GATE(y), GATE(w));
#undef GATE
                __syncwarp();
            }
            const uint64_t ap = (uint64_t)(sc->acc + b * 512 + tid), op = (uint64_t)(out + b * DM + 2 * tid);
            const uint64_t sp = (uint64_t)(sc->sx + (b * NH + h) * 256 + tid);
            sts128(sb + SM_FIN + tid * 16, make_uint4((uint32_t)ap, ap >> 32, (uint32_t)sp, sp >> 32));
            sts128(sb + SM_FIN + 4096 + tid * 16, make_uint4((uint32_t)op, op >> 32, gw, xw));
        });
        float acc[4][4] = {};
        uint4 fin0, fin1;
#pragma unroll
        for (int kk = 0; kk < 4; kk++) {
            const uint4 b = lds128(sb + SM_O + (kk * 32 + 8 * t) * 2);
            if (kk == 3) { fin0 = lds128(sb + SM_FIN + tid * 16); fin1 = lds128(sb + SM_FIN + 4096 + tid * 16); }
#pragma unroll
            for (int i = 0; i < 4; i++) mma(acc[i], wof[2 * kk][i][0], wof[2 * kk][i][1], wof[2 * kk][i][2], wof[2 * kk][i][3], b.x, b.y);
#pragma unroll
            for (int i = 0; i < 4; i++) mma(acc[i], wof[2 * kk + 1][i][0], wof[2 * kk + 1][i][1], wof[2 * kk + 1][i][2], wof[2 * kk + 1][i][3], b.z, b.w);
        }
        const uint64_t ap = (uint64_t)fin0.y << 32 | fin0.x, sp = (uint64_t)fin0.w << 32 | fin0.z, op = (uint64_t)fin1.y << 32 | fin1.x;
        const float va = (t & 2) ? ((t & 1) ? acc[3][0] : acc[2][0]) : ((t & 1) ? acc[1][0] : acc[0][0]);
        const float vb = (t & 2) ? ((t & 1) ? acc[3][2] : acc[2][2]) : ((t & 1) ? acc[1][2] : acc[0][2]);
        const unsigned long long fa = to_fixed(va), fb = to_fixed(vb);
        uint32_t alo, ahi, blo, bhi;
        asm volatile("{ .reg .b64 ta, tb;\n"
                     "st.relaxed.gpu.global.v2.u32 [%5], {%6,%7};\n"
                     "atom.relaxed.gpu.global.add.u64 ta, [%4], %8;\n"
                     "atom.relaxed.gpu.global.add.u64 tb, [%4+2048], %9;\n"
                     "add.u64 ta, ta, %8;\n"
                     "add.u64 tb, tb, %9;\n"
                     "mov.b64 {%0,%1}, ta;\n"
                     "mov.b64 {%2,%3}, tb; }"
                     : "=r"(alo), "=r"(ahi), "=r"(blo), "=r"(bhi)
                     : "l"(ap), "l"(sp), "r"((__float_as_uint(va) & ~3u) | tag), "r"((__float_as_uint(vb) & ~3u) | tag),
                       "l"(fa), "l"(fb) : "memory");
        const float s0 = from_fixed(alo, ahi), s1 = from_fixed(blo, bhi);
        uint32_t ow = combine(s0, s1, fin1.z, fin1.w);
        const bool last_a = alo & NH, last_b = blo & NH;
        if (last_a) st_out(op, ow);
        if (last_b) st_out(op + 2, ow >> 16);
        const bool redo_a = last_a & needs_fp32(alo, s0), redo_b = last_b & needs_fp32(blo, s1);
        if (redo_a | redo_b) {
            const float2 s = sum_fp32((const uint2*)sp - h * 256, tag);
            ow = combine(s.x, s.y, fin1.z, fin1.w);
            if (redo_a) st_out(op, ow);
            if (redo_b) st_out(op + 2, ow >> 16);
        }
        __syncwarp();
    }
}

__global__ void __launch_bounds__(NTHREADS, 1)
fused_decode_kernel(const bf16* __restrict__ x, const bf16* __restrict__ kc, const bf16* __restrict__ vc,
                    const bf16* __restrict__ wq, const bf16* __restrict__ wo, const bf16* __restrict__ wg,
                    const bf16* __restrict__ wu, const bf16* __restrict__ wd, bf16* __restrict__ out, Scratch* sc) {
    extern __shared__ __align__(128) unsigned char smem[];
    const uint32_t sb = (uint32_t)__cvta_generic_to_shared(smem);
    const int warp = threadIdx.x >> 5, lane = threadIdx.x & 31;
    const int h = blockIdx.x >> 2, j = blockIdx.x & 3;
    asm volatile("prefetch.global.L2 [%0];" :: "l"((const char*)wq + blockIdx.x * TILE_BYTES + threadIdx.x * 64));
    if (threadIdx.x == 0) {
        const char* k0 = cache_of(kc, h, j, 0);
        const uint64_t pol = stream_policy();
#pragma unroll
        for (int s = 1; s <= DEPTH1; s++) {
            mbar_init(sb + SM_FULL + s * 8, 1);
            asm volatile("fence.mbarrier_init.release.cluster;" ::: "memory");
            mbar_expect_tx(sb + SM_FULL + s * 8, TILE_BYTES);
            bulk_load(sb + s * TILE_BYTES, k0 + (s - 1) * TILE_BYTES, TILE_BYTES, sb + SM_FULL + s * 8, pol);
        }
    }
    if (warp < 4) {
        asm volatile("setmaxnreg.dec.sync.aligned.u32 88;");
        if (warp == 0) {
            if (lane == 0) {
#pragma unroll
                for (int s = 0; s < STAGES; s++) {
                    if (s == 0 || s > DEPTH1) mbar_init(sb + SM_FULL + s * 8, 1);
                    mbar_init(sb + SM_EMPTY + s * 8, 8);
                }
#pragma unroll
                for (int w = 0; w < 8; w++) mbar_init(sb + SM_LAST + w * 8, 1);
                asm volatile("fence.mbarrier_init.release.cluster;" ::: "memory");
                mbar_arrive(sb + SM_FULL);
            }
            __syncwarp();
            asm volatile("bar.arrive 2, 320;" ::: "memory");
            if (lane == 0) producer(sb, h, j, kc, vc, wo, sc);
        } else if (warp == 1) {
            glu_warp(sb, h, j, wg, wu, wd, sc);
        }
    } else {
        consumer(sb, h, j, x, wq, out, sc);
    }
}

}

extern "C" void kernel_launch(void* const* d_in, const int* in_sizes, int n_in, void* d_out, int out_size) {
    static Scratch* scratch = nullptr;
    if (!scratch) {
        cudaFuncSetAttribute(fused_decode_kernel, cudaFuncAttributeMaxDynamicSharedMemorySize, SM_TOTAL);
        cudaGetSymbolAddress((void**)&scratch, g_scratch);
    }
    fused_decode_kernel<<<NCTA, NTHREADS, SM_TOTAL>>>(
        (const bf16*)d_in[0], (const bf16*)d_in[1], (const bf16*)d_in[2], (const bf16*)d_in[3], (const bf16*)d_in[4],
        (const bf16*)d_in[6], (const bf16*)d_in[7], (const bf16*)d_in[8], (bf16*)d_out, scratch);
}
```
